```python
import torch

def _softmax(x, axis=-1):
    return torch.softmax(x, dim=axis)
def _gelu(x):
    return torch.nn.functional.gelu(x, approximate="tanh")
def _silu(x):
    return torch.nn.functional.silu(x)
def _sigmoid(x):
    return torch.sigmoid(x)
def _layernorm(x, axis=-1, eps=1e-5):
    m = x.mean(dim=axis, keepdim=True)
    v = x.var(dim=axis, keepdim=True, unbiased=False)
    return (x - m) / torch.sqrt(v + eps)
def _scatter_add(tgt, idx, src, axis=0):
    return tgt.clone().index_add_(axis, idx, src)
def _segment_sum(src, seg, n):
    out = torch.zeros((n,) + src.shape[1:], dtype=src.dtype)
    return out.index_add_(0, seg, src)
def _pad(x, pw):
    flat = tuple(v for pair in reversed(pw) for v in pair)
    return torch.nn.functional.pad(x, flat)

kernel_name = 'recurrent_scan__mha_block_cached__mixer_token_mlp__prompt'

def setup_inputs():

    _w = (lambda a: (lambda t: t.to(torch.bfloat16) if t.is_floating_point() else t)(torch.as_tensor(a)))
    def _A_setup():
        B, Sq, D = 1, 2048, 640
        H, Sk, Dh = 32, 2048, 128
        return {
            "x": _w((lambda *s: torch.randn(*s, dtype=torch.bfloat16) * 0.1)(B, Sq, D)),
            "k_cache": _w((lambda *s: torch.randn(*s, dtype=torch.bfloat16) * 0.8)(B, H, Sk, Dh)),
            "v_cache": _w((lambda *s: torch.randn(*s, dtype=torch.bfloat16) * 3.2)(B, H, Sk, Dh)),
            "wq": _w((lambda *s: torch.randn(*s, dtype=torch.bfloat16) * 0.8)(D, H * Dh) * (D ** -0.5)),
            "wo": _w((lambda *s: torch.randn(*s, dtype=torch.bfloat16) * 3.2)(H * Dh, D) * ((H * Dh) ** -0.5)),
        }
    _A_in = _A_setup()

    def _B_setup():
        B, S, D, F = 1, 2048, 640, 1728
        return {
            "x": _w((lambda *s: torch.randn(*s, dtype=torch.bfloat16) * 0.1)(B, S, D)),
            "w1": _w((lambda *s: torch.randn(*s, dtype=torch.bfloat16) * 3.2)(S, F) * (S ** -0.5)),
            "b1": _w((lambda *s: torch.randn(*s, dtype=torch.bfloat16) * 3.2)(F) * 0.02),
            "w2": _w((lambda *s: torch.randn(*s, dtype=torch.bfloat16) * 3.2)(F, S) * (F ** -0.5)),
            "b2": _w((lambda *s: torch.randn(*s, dtype=torch.bfloat16) * 3.2)(S) * 0.02),
        }
    _B_in = _B_setup()

    return {
        "A_x": _A_in["x"],
        "A_k_cache": _A_in["k_cache"],
        "A_v_cache": _A_in["v_cache"],
        "A_wq": _A_in["wq"],
        "A_wo": _A_in["wo"],
        "B_x": _B_in["x"],
        "B_w1": _B_in["w1"],
        "B_b1": _B_in["b1"],
        "B_w2": _B_in["w2"],
        "B_b2": _B_in["b2"],
    }

def reference(A_x, A_k_cache, A_v_cache, A_wq, A_wo, B_x, B_w1, B_b1, B_w2, B_b2):
    def _A_ref(x, k_cache, v_cache, wq, wo):
        B, Sq, D = x.shape
        H, Dh = 32, 128
        q = (lambda x, *d: x.permute(*d))((x @ wq).reshape(B, Sq, H, Dh), 0, 2, 1, 3)
        scores = torch.einsum("bhqd,bhkd->bhqk", q, k_cache) * (Dh ** -0.5)
        p = _softmax(scores, axis=-1)
        o = torch.einsum("bhqk,bhkd->bhqd", p, v_cache)
        return (lambda x, *d: x.permute(*d))(o, 0, 2, 1, 3).reshape(B, Sq, H * Dh) @ wo

    def _B_ref(x, w1, b1, w2, b2):
        B, S, D = x.shape
        h = _layernorm(x, axis=-1)
        u = torch.einsum("bsd,sf->bdf", h, w1) + b1
        u = _gelu(u)
        y = torch.einsum("bdf,fs->bds", u, w2) + b2
        return (lambda x, *d: x.permute(*d))(y, 0, 2, 1)

    x = A_x
    xn = _layernorm(x, axis=-1)
    s = _A_ref(xn, A_k_cache, A_v_cache, A_wq, A_wo)
    g = _silu(_B_ref(xn, B_w1, B_b1, B_w2, B_b2))
    return x + s * g
```

```cpp
#include <cuda_runtime.h>
#include <cuda_bf16.h>
#include <cuda.h>
#include <stdint.h>

typedef __nv_bfloat16 bf16;
constexpr int SEQ = 2048, DM = 640, NH = 32, DH = 128, FF = 1728;

__device__ bf16 g_xn[SEQ * DM];
__device__ bf16 g_h[SEQ * DM];
__device__ bf16 g_o[SEQ * NH * DH];
__device__ bf16 g_ut[FF * DM];
__device__ float4 g_part[32 * 3 * 2 * 20 * 256];
constexpr int C_XN = 0, C_H = 16, C_DONE = 17, C_U = 32, C_PART = 64, C_O = 256, C_TOTAL = 256 + 512;
__device__ uint32_t g_cnt[C_TOTAL];

__device__ __forceinline__ uint32_t smem_u32(const void* p) { return (uint32_t)__cvta_generic_to_shared(p); }
__device__ __forceinline__ void mbar_init(uint32_t bar, uint32_t cnt) { asm volatile("mbarrier.init.shared::cta.b64 [%0], %1;" :: "r"(bar), "r"(cnt)); }
__device__ __forceinline__ void mbar_expect_tx(uint32_t bar, uint32_t bytes) { asm volatile("mbarrier.arrive.expect_tx.shared::cta.b64 _, [%0], %1;" :: "r"(bar), "r"(bytes) : "memory"); }
__device__ __forceinline__ void mbar_arrive(uint32_t bar) { asm volatile("mbarrier.arrive.shared::cta.b64 _, [%0];" :: "r"(bar) : "memory"); }
__device__ __forceinline__ void mbar_arrive_cluster(uint32_t bar, uint32_t cta) {
  asm volatile("{\n.reg .b32 ra;\nmapa.shared::cluster.u32 ra, %0, %1;\nmbarrier.arrive.shared::cluster.b64 _, [ra];\n}" :: "r"(bar), "r"(cta) : "memory"); }
__device__ __forceinline__ bool mbar_try_wait(uint32_t bar, uint32_t parity) {
  uint32_t ok;
  asm volatile("{\n.reg .pred p;\nmbarrier.try_wait.parity.shared::cta.b64 p, [%1], %2;\nselp.b32 %0, 1, 0, p;\n}" : "=r"(ok) : "r"(bar), "r"(parity) : "memory");
  return ok; }
__device__ __forceinline__ void mbar_wait(uint32_t bar, uint32_t parity) {
  asm volatile("{\n.reg .pred p;\n.reg .u32 n;\nmov.u32 n, 0;\n"
               "LAB_WAIT:\n"
               "mbarrier.try_wait.parity.shared::cta.b64 p, [%0], %1;\n"
               "@p bra LAB_DONE;\n"
               "add.u32 n, n, 1;\n"
               "setp.lt.u32 p, n, 0x1000000;\n"
               "@p bra LAB_WAIT;\n"
               "trap;\n"
               "LAB_DONE:\n}" :: "r"(bar), "r"(parity) : "memory"); }
__device__ __forceinline__ void tma_load_2d(uint32_t dst, const CUtensorMap* map, int c0, int c1, uint32_t bar) {
  asm volatile("cp.async.bulk.tensor.2d.shared::cluster.global.mbarrier::complete_tx::bytes [%0], [%1, {%3, %4}], [%2];"
    :: "r"(dst), "l"(map), "r"(bar), "r"(c0), "r"(c1) : "memory"); }
__device__ __forceinline__ void tma_load_2d_mc(uint32_t dst, const CUtensorMap* map, int c0, int c1, uint32_t bar, uint16_t mask) {
  asm volatile("cp.async.bulk.tensor.2d.shared::cluster.global.mbarrier::complete_tx::bytes.multicast::cluster [%0], [%1, {%3, %4}], [%2], %5;"
    :: "r"(dst), "l"(map), "r"(bar), "r"(c0), "r"(c1), "h"(mask) : "memory"); }
__device__ __forceinline__ void tma_store_2d(const CUtensorMap* map, uint32_t src, int c0, int c1) {
  asm volatile("cp.async.bulk.tensor.2d.global.shared::cta.bulk_group [%0, {%2, %3}], [%1];" :: "l"(map), "r"(src), "r"(c0), "r"(c1) : "memory"); }
__device__ __forceinline__ void bulk_commit() { asm volatile("cp.async.bulk.commit_group;" ::: "memory"); }
template<int N> __device__ __forceinline__ void bulk_wait_read() { asm volatile("cp.async.bulk.wait_group.read %0;" :: "n"(N) : "memory"); }
template<int N> __device__ __forceinline__ void bulk_wait() { asm volatile("cp.async.bulk.wait_group %0;" :: "n"(N) : "memory"); }
__device__ __forceinline__ void fence_async_smem() { asm volatile("fence.proxy.async.shared::cta;" ::: "memory"); }
__device__ __forceinline__ void wgmma_fence() { asm volatile("wgmma.fence.sync.aligned;" ::: "memory"); }
__device__ __forceinline__ void wgmma_commit() { asm volatile("wgmma.commit_group.sync.aligned;" ::: "memory"); }
template<int N> __device__ __forceinline__ void wgmma_wait() { asm volatile("wgmma.wait_group.sync.aligned %0;" :: "n"(N) : "memory"); }
__device__ __forceinline__ uint64_t make_desc(uint32_t addr, uint32_t lbo, uint32_t sbo) {
  return (uint64_t)((addr & 0x3FFFF) >> 4) | ((uint64_t)(lbo >> 4) << 16) | ((uint64_t)(sbo >> 4) << 32) | (1ull << 62); }
__device__ __forceinline__ uint32_t cluster_ctarank() { uint32_t r; asm volatile("mov.u32 %0, %%cluster_ctarank;" : "=r"(r)); return r; }
__device__ __forceinline__ void cluster_arrive() { asm volatile("barrier.cluster.arrive.release.aligned;" ::: "memory"); }
__device__ __forceinline__ void cluster_wait() { asm volatile("barrier.cluster.wait.acquire.aligned;" ::: "memory"); }
__device__ __forceinline__ void bar_sync(int id, int n) { asm volatile("bar.sync %0, %1;" :: "r"(id), "r"(n) : "memory"); }
__device__ __forceinline__ void bar_arrive(int id, int n) { asm volatile("bar.arrive %0, %1;" :: "r"(id), "r"(n) : "memory"); }
__device__ __forceinline__ float ex2(float x) { float y; asm("ex2.approx.ftz.f32 %0, %1;" : "=f"(y) : "f"(x)); return y; }
__device__ __forceinline__ uint32_t pack_bf16(float lo, float hi) { uint32_t r; asm("cvt.rn.bf16x2.f32 %0, %1, %2;" : "=r"(r) : "f"(hi), "f"(lo)); return r; }
__device__ __forceinline__ float rbf16(float x) { return __bfloat162float(__float2bfloat16(x)); }
__device__ __forceinline__ void stmatrix_x4(uint32_t addr, uint32_t r0, uint32_t r1, uint32_t r2, uint32_t r3) {
  asm volatile("stmatrix.sync.aligned.m8n8.x4.shared.b16 [%0], {%1, %2, %3, %4};" :: "r"(addr), "r"(r0), "r"(r1), "r"(r2), "r"(r3) : "memory"); }
template<int R> __device__ __forceinline__ void fence_regs(float (&a)[R]) {
#pragma unroll
  for (int i = 0; i < R; i++) asm volatile("" : "+f"(a[i]) :: "memory"); }

__device__ __forceinline__ void sched_fence(float v) {
  asm volatile("{\n.reg .pred p;\nLAB_SF:\nsetp.lt.f32 p, %0, 0f00000000;\n@p bra LAB_SF;\n}" :: "f"(v) : "memory"); }

__device__ __forceinline__ void tma_load_3d_mc(uint32_t dst, const CUtensorMap* map, int c0, int c1, int c2, uint32_t bar, uint16_t mask) {
  asm volatile("cp.async.bulk.tensor.3d.shared::cluster.global.mbarrier::complete_tx::bytes.multicast::cluster [%0], [%1, {%3, %4, %5}], [%2], %6;"
    :: "r"(dst), "l"(map), "r"(bar), "r"(c0), "r"(c1), "r"(c2), "h"(mask) : "memory"); }
__device__ __forceinline__ void bulk_load(uint32_t dst, const void* src, uint32_t bytes, uint32_t bar) {
  asm volatile("cp.async.bulk.shared::cluster.global.mbarrier::complete_tx::bytes [%0], [%1], %2, [%3];" :: "r"(dst), "l"(src), "r"(bytes), "r"(bar) : "memory"); }
__device__ __forceinline__ void fence_async_global() { asm volatile("fence.proxy.async.global;" ::: "memory"); }
__device__ __forceinline__ void cluster_arrive_relaxed() { asm volatile("barrier.cluster.arrive.relaxed.aligned;" ::: "memory"); }
__device__ __forceinline__ void tma_load_3d(uint32_t dst, const CUtensorMap* map, int c0, int c1, int c2, uint32_t bar) {
  asm volatile("cp.async.bulk.tensor.3d.shared::cluster.global.mbarrier::complete_tx::bytes [%0], [%1, {%3, %4, %5}], [%2];"
    :: "r"(dst), "l"(map), "r"(bar), "r"(c0), "r"(c1), "r"(c2) : "memory"); }
__device__ __forceinline__ void ldmatrix_x4(uint32_t addr, uint32_t& r0, uint32_t& r1, uint32_t& r2, uint32_t& r3) {
  asm volatile("ldmatrix.sync.aligned.m8n8.x4.shared.b16 {%0, %1, %2, %3}, [%4];" : "=r"(r0), "=r"(r1), "=r"(r2), "=r"(r3) : "r"(addr) : "memory"); }
__device__ __forceinline__ uint32_t bf2_add(uint32_t a, uint32_t b) { uint32_t r; asm("add.rn.bf16x2 %0, %1, %2;" : "=r"(r) : "r"(a), "r"(b)); return r; }
__device__ __forceinline__ uint32_t bf2_sub(uint32_t a, uint32_t b) { uint32_t r; asm("sub.rn.bf16x2 %0, %1, %2;" : "=r"(r) : "r"(a), "r"(b)); return r; }
__device__ __forceinline__ uint32_t bf2_mul(uint32_t a, uint32_t b) { uint32_t r; asm("mul.rn.bf16x2 %0, %1, %2;" : "=r"(r) : "r"(a), "r"(b)); return r; }
__device__ __forceinline__ float bf_lo(uint32_t v) { return __uint_as_float(v << 16); }
__device__ __forceinline__ float bf_hi(uint32_t v) { return __uint_as_float(v & 0xffff0000u); }
__device__ __forceinline__ float rcp_fast(float x) { float y; asm("rcp.approx.ftz.f32 %0, %1;" : "=f"(y) : "f"(x)); return y; }
__device__ __forceinline__ float sqrt_fast(float x) { float y; asm("sqrt.approx.ftz.f32 %0, %1;" : "=f"(y) : "f"(x)); return y; }
__device__ __forceinline__ uint32_t ld_acquire(const uint32_t* p) { uint32_t v; asm volatile("ld.acquire.gpu.global.u32 %0, [%1];" : "=r"(v) : "l"(p) : "memory"); return v; }
__device__ __forceinline__ void red_release(uint32_t* p, uint32_t v) { asm volatile("red.release.gpu.global.add.u32 [%0], %1;" :: "l"(p), "r"(v) : "memory"); }
__device__ __forceinline__ uint64_t make_desc64(uint32_t addr, uint32_t lbo, uint32_t sbo) {
  return (uint64_t)((addr & 0x3FFFF) >> 4) | ((uint64_t)(lbo >> 4) << 16) | ((uint64_t)(sbo >> 4) << 32) | (2ull << 62); }

template<int R> __device__ __forceinline__ void zero_regs(float (&a)[R]) {
#pragma unroll
  for (int i = 0; i < R; i++) a[i] = 0.f; }

__device__ __forceinline__ void tma_store_3d(const CUtensorMap* map, uint32_t src, int c0, int c1, int c2) {
  asm volatile("cp.async.bulk.tensor.3d.global.shared::cta.bulk_group [%0, {%2, %3, %4}], [%1];" :: "l"(map), "r"(src), "r"(c0), "r"(c1), "r"(c2) : "memory"); }
__device__ __forceinline__ void tma_prefetch_2d(const CUtensorMap* map, int c0, int c1) {
  asm volatile("cp.async.bulk.prefetch.tensor.2d.L2.global [%0, {%1, %2}];" :: "l"(map), "r"(c0), "r"(c1) : "memory"); }
__device__ __forceinline__ void prefetch_map(const CUtensorMap* map) { asm volatile("prefetch.tensormap [%0];" :: "l"(map) : "memory"); }
__device__ __forceinline__ void mbar_arrive_cluster_n(uint32_t bar, uint32_t cta, uint32_t n) {
  asm volatile("{\n.reg .b32 ra;\nmapa.shared::cluster.u32 ra, %0, %1;\nmbarrier.arrive.shared::cluster.b64 _, [ra], %2;\n}" :: "r"(bar), "r"(cta), "r"(n) : "memory"); }
__device__ __forceinline__ void wait_flags(uint32_t& mask, int bit, const uint32_t* cnt, int n, uint32_t target, int lane) {
  if (mask >> bit & 1) return;
  _Pragma("unroll 1") for (uint32_t spin = 0; spin < 0x400000; spin++) {
    const bool ok = lane < n && ld_acquire(cnt + lane) >= target;
    mask = __ballot_sync(0xffffffffu, ok);
    if (mask >> bit & 1) break;
    __nanosleep(40);
  }
  __syncwarp();
  fence_async_global();
}

__device__ __forceinline__ void tma_load_2d_mc_hint(uint32_t dst, const CUtensorMap* map, int c0, int c1, uint32_t bar, uint16_t mask, uint64_t pol) {
  asm volatile("cp.async.bulk.tensor.2d.shared::cluster.global.mbarrier::complete_tx::bytes.multicast::cluster.L2::cache_hint [%0], [%1, {%3, %4}], [%2], %5, %6;"
    :: "r"(dst), "l"(map), "r"(bar), "r"(c0), "r"(c1), "h"(mask), "l"(pol) : "memory"); }
__device__ __forceinline__ void bulk_prefetch(const void* src, uint32_t bytes) {
  asm volatile("cp.async.bulk.prefetch.L2.global [%0], %1;" :: "l"(src), "r"(bytes) : "memory"); }
__device__ __forceinline__ void prefetch_share(const void* p, uint32_t total, int lane) {
  const uint32_t piece = total / (128 * 32);
  if (blockIdx.x < 128) bulk_prefetch((const char*)p + (blockIdx.x * 32 + lane) * piece, piece);
}

__device__ __forceinline__ bool elect_one() {
  uint32_t p; asm volatile("{\n.reg .pred P;\nelect.sync _|P, 0xffffffff;\nselp.b32 %0, 1, 0, P;\n}" : "=r"(p)); return p; }
__device__ __forceinline__ void prefetch_l1(const void* p) { asm volatile("prefetch.global.L1 [%0];" :: "l"(p)); }

template<int TB> __device__ __forceinline__ void wgmma_rs_n64(float (&d)[32], const uint32_t (&a)[4], uint64_t db, int scale_d) {
  asm volatile("{\n.reg .pred p;\n"
    "setp.ne.b32 p, %37, 0;\n"
    "wgmma.mma_async.sync.aligned.m64n64k16.f32.bf16.bf16 "
    "{%0, %1, %2, %3, %4, %5, %6, %7, %8, %9, %10, %11, %12, %13, %14, %15, %16, %17, %18, %19, %20, %21, %22, %23, %24, %25, %26, %27, %28, %29, %30, %31}, "
    "{%32, %33, %34, %35}, %36, p, 1, 1, %38;\n}\n"
    : "+f"(d[0]), "+f"(d[1]), "+f"(d[2]), "+f"(d[3]), "+f"(d[4]), "+f"(d[5]), "+f"(d[6]), "+f"(d[7]), "+f"(d[8]), "+f"(d[9]), "+f"(d[10]), "+f"(d[11]), "+f"(d[12]), "+f"(d[13]), "+f"(d[14]), "+f"(d[15]), "+f"(d[16]), "+f"(d[17]), "+f"(d[18]), "+f"(d[19]), "+f"(d[20]), "+f"(d[21]), "+f"(d[22]), "+f"(d[23]), "+f"(d[24]), "+f"(d[25]), "+f"(d[26]), "+f"(d[27]), "+f"(d[28]), "+f"(d[29]), "+f"(d[30]), "+f"(d[31])
    : "r"(a[0]), "r"(a[1]), "r"(a[2]), "r"(a[3]), "l"(db), "r"(scale_d), "n"(TB));
}
template<int TB> __device__ __forceinline__ void wgmma_rs_n128(float (&d)[64], const uint32_t (&a)[4], uint64_t db, int scale_d) {
  asm volatile("{\n.reg .pred p;\n"
    "setp.ne.b32 p, %69, 0;\n"
    "wgmma.mma_async.sync.aligned.m64n128k16.f32.bf16.bf16 "
    "{%0, %1, %2, %3, %4, %5, %6, %7, %8, %9, %10, %11, %12, %13, %14, %15, %16, %17, %18, %19, %20, %21, %22, %23, %24, %25, %26, %27, %28, %29, %30, %31, %32, %33, %34, %35, %36, %37, %38, %39, %40, %41, %42, %43, %44, %45, %46, %47, %48, %49, %50, %51, %52, %53, %54, %55, %56, %57, %58, %59, %60, %61, %62, %63}, "
    "{%64, %65, %66, %67}, %68, p, 1, 1, %70;\n}\n"
    : "+f"(d[0]), "+f"(d[1]), "+f"(d[2]), "+f"(d[3]), "+f"(d[4]), "+f"(d[5]), "+f"(d[6]), "+f"(d[7]), "+f"(d[8]), "+f"(d[9]), "+f"(d[10]), "+f"(d[11]), "+f"(d[12]), "+f"(d[13]), "+f"(d[14]), "+f"(d[15]), "+f"(d[16]), "+f"(d[17]), "+f"(d[18]), "+f"(d[19]), "+f"(d[20]), "+f"(d[21]), "+f"(d[22]), "+f"(d[23]), "+f"(d[24]), "+f"(d[25]), "+f"(d[26]), "+f"(d[27]), "+f"(d[28]), "+f"(d[29]), "+f"(d[30]), "+f"(d[31]), "+f"(d[32]), "+f"(d[33]), "+f"(d[34]), "+f"(d[35]), "+f"(d[36]), "+f"(d[37]), "+f"(d[38]), "+f"(d[39]), "+f"(d[40]), "+f"(d[41]), "+f"(d[42]), "+f"(d[43]), "+f"(d[44]), "+f"(d[45]), "+f"(d[46]), "+f"(d[47]), "+f"(d[48]), "+f"(d[49]), "+f"(d[50]), "+f"(d[51]), "+f"(d[52]), "+f"(d[53]), "+f"(d[54]), "+f"(d[55]), "+f"(d[56]), "+f"(d[57]), "+f"(d[58]), "+f"(d[59]), "+f"(d[60]), "+f"(d[61]), "+f"(d[62]), "+f"(d[63])
    : "r"(a[0]), "r"(a[1]), "r"(a[2]), "r"(a[3]), "l"(db), "r"(scale_d), "n"(TB));
}
template<int TA, int TB> __device__ __forceinline__ void wgmma_ss_n128(float (&d)[64], uint64_t da, uint64_t db, int scale_d) {
  asm volatile("{\n.reg .pred p;\n"
    "setp.ne.b32 p, %66, 0;\n"
    "wgmma.mma_async.sync.aligned.m64n128k16.f32.bf16.bf16 "
    "{%0, %1, %2, %3, %4, %5, %6, %7, %8, %9, %10, %11, %12, %13, %14, %15, %16, %17, %18, %19, %20, %21, %22, %23, %24, %25, %26, %27, %28, %29, %30, %31, %32, %33, %34, %35, %36, %37, %38, %39, %40, %41, %42, %43, %44, %45, %46, %47, %48, %49, %50, %51, %52, %53, %54, %55, %56, %57, %58, %59, %60, %61, %62, %63}, "
    "%64, %65, p, 1, 1, %67, %68;\n}\n"
    : "+f"(d[0]), "+f"(d[1]), "+f"(d[2]), "+f"(d[3]), "+f"(d[4]), "+f"(d[5]), "+f"(d[6]), "+f"(d[7]), "+f"(d[8]), "+f"(d[9]), "+f"(d[10]), "+f"(d[11]), "+f"(d[12]), "+f"(d[13]), "+f"(d[14]), "+f"(d[15]), "+f"(d[16]), "+f"(d[17]), "+f"(d[18]), "+f"(d[19]), "+f"(d[20]), "+f"(d[21]), "+f"(d[22]), "+f"(d[23]), "+f"(d[24]), "+f"(d[25]), "+f"(d[26]), "+f"(d[27]), "+f"(d[28]), "+f"(d[29]), "+f"(d[30]), "+f"(d[31]), "+f"(d[32]), "+f"(d[33]), "+f"(d[34]), "+f"(d[35]), "+f"(d[36]), "+f"(d[37]), "+f"(d[38]), "+f"(d[39]), "+f"(d[40]), "+f"(d[41]), "+f"(d[42]), "+f"(d[43]), "+f"(d[44]), "+f"(d[45]), "+f"(d[46]), "+f"(d[47]), "+f"(d[48]), "+f"(d[49]), "+f"(d[50]), "+f"(d[51]), "+f"(d[52]), "+f"(d[53]), "+f"(d[54]), "+f"(d[55]), "+f"(d[56]), "+f"(d[57]), "+f"(d[58]), "+f"(d[59]), "+f"(d[60]), "+f"(d[61]), "+f"(d[62]), "+f"(d[63])
    : "l"(da), "l"(db), "r"(scale_d), "n"(TA), "n"(TB));
}
template<int TA, int TB> __device__ __forceinline__ void wgmma_ss_n160(float (&d)[80], uint64_t da, uint64_t db, int scale_d) {
  asm volatile("{\n.reg .pred p;\n"
    "setp.ne.b32 p, %82, 0;\n"
    "wgmma.mma_async.sync.aligned.m64n160k16.f32.bf16.bf16 "
    "{%0, %1, %2, %3, %4, %5, %6, %7, %8, %9, %10, %11, %12, %13, %14, %15, %16, %17, %18, %19, %20, %21, %22, %23, %24, %25, %26, %27, %28, %29, %30, %31, %32, %33, %34, %35, %36, %37, %38, %39, %40, %41, %42, %43, %44, %45, %46, %47, %48, %49, %50, %51, %52, %53, %54, %55, %56, %57, %58, %59, %60, %61, %62, %63, %64, %65, %66, %67, %68, %69, %70, %71, %72, %73, %74, %75, %76, %77, %78, %79}, "
    "%80, %81, p, 1, 1, %83, %84;\n}\n"
    : "+f"(d[0]), "+f"(d[1]), "+f"(d[2]), "+f"(d[3]), "+f"(d[4]), "+f"(d[5]), "+f"(d[6]), "+f"(d[7]), "+f"(d[8]), "+f"(d[9]), "+f"(d[10]), "+f"(d[11]), "+f"(d[12]), "+f"(d[13]), "+f"(d[14]), "+f"(d[15]), "+f"(d[16]), "+f"(d[17]), "+f"(d[18]), "+f"(d[19]), "+f"(d[20]), "+f"(d[21]), "+f"(d[22]), "+f"(d[23]), "+f"(d[24]), "+f"(d[25]), "+f"(d[26]), "+f"(d[27]), "+f"(d[28]), "+f"(d[29]), "+f"(d[30]), "+f"(d[31]), "+f"(d[32]), "+f"(d[33]), "+f"(d[34]), "+f"(d[35]), "+f"(d[36]), "+f"(d[37]), "+f"(d[38]), "+f"(d[39]), "+f"(d[40]), "+f"(d[41]), "+f"(d[42]), "+f"(d[43]), "+f"(d[44]), "+f"(d[45]), "+f"(d[46]), "+f"(d[47]), "+f"(d[48]), "+f"(d[49]), "+f"(d[50]), "+f"(d[51]), "+f"(d[52]), "+f"(d[53]), "+f"(d[54]), "+f"(d[55]), "+f"(d[56]), "+f"(d[57]), "+f"(d[58]), "+f"(d[59]), "+f"(d[60]), "+f"(d[61]), "+f"(d[62]), "+f"(d[63]), "+f"(d[64]), "+f"(d[65]), "+f"(d[66]), "+f"(d[67]), "+f"(d[68]), "+f"(d[69]), "+f"(d[70]), "+f"(d[71]), "+f"(d[72]), "+f"(d[73]), "+f"(d[74]), "+f"(d[75]), "+f"(d[76]), "+f"(d[77]), "+f"(d[78]), "+f"(d[79])
    : "l"(da), "l"(db), "r"(scale_d), "n"(TA), "n"(TB));
}

#define ITEMCLK(i)
#define CLKS()
#define PROF(id)
#define PROF_ARGS
#define PROF_PASS
__device__ __forceinline__ void ln_row(uint32_t (&v)[20]) {
  float s = 0.f;
#pragma unroll
  for (int i = 0; i < 20; i++) s += bf_lo(v[i]) + bf_hi(v[i]);
#pragma unroll
  for (int o = 8; o > 0; o >>= 1) s += __shfl_xor_sync(0xffffffffu, s, o);
  const float mean = s * (1.f / DM);
  float q = 0.f;
#pragma unroll
  for (int i = 0; i < 20; i++) { const float d0 = bf_lo(v[i]) - mean, d1 = bf_hi(v[i]) - mean; q = fmaf(d0, d0, q); q = fmaf(d1, d1, q); }
#pragma unroll
  for (int o = 8; o > 0; o >>= 1) q += __shfl_xor_sync(0xffffffffu, q, o);
  const uint32_t mb = pack_bf16(mean, mean);
  const float inv = rcp_fast(rbf16(sqrt_fast(rbf16(rbf16(q * (1.f / DM)) + 1e-5f))));
#pragma unroll
  for (int i = 0; i < 20; i++) { const uint32_t d = bf2_sub(v[i], mb); v[i] = pack_bf16(bf_lo(d) * inv, bf_hi(d) * inv); }
}

constexpr int NST = 6;
constexpr int STAGE = 36864;
constexpr int SMEM_BYTES = NST * STAGE + 1024 + 256 + 1024;
struct Ring {
  uint32_t stage, phase;
  __device__ __forceinline__ void advance() { if (++stage == NST) { stage = 0; phase ^= 1; } }
  __device__ __forceinline__ void skip(int n) { stage = (stage + n) % NST; }
};
constexpr float SCALE_LOG2E = 0.08838834764831845f * 1.4426950408889634f;
#define LAZY_SUM 4096.0f
#define PART_D 34
#define PF_ITEM 3
#define CREGS "232"
#define PREGS "40"

enum { T_END = 0, T_ATT = 1, T_MLP1 = 2, T_PART = 3, T_OWN = 4 };
constexpr int NCL = 66, MAXI = 8;
struct Params {
  CUtensorMap xn, wq, k, v, o, wo, w1, h, w2, ut, ut_st, out_st, x_ld;
  const bf16 *x, *b1, *b2, *pw1, *pw2, *pwo;
  uint32_t sched[NCL][MAXI];
};
constexpr int PART_PIECE = 7 * 4096;

__device__ __forceinline__ void release_stage(uint32_t empty_bar, int lane) {
  if (lane < 2) mbar_arrive_cluster(empty_bar, lane);
}
__device__ __forceinline__ void row_max(const float (&s)[32], float& mx0, float& mx1) {
  mx0 = fmaxf(s[0], s[1]); mx1 = fmaxf(s[2], s[3]);
  float mx0b = fmaxf(s[4], s[5]), mx1b = fmaxf(s[6], s[7]);
#pragma unroll
  for (int j = 2; j < 8; j += 2) {
    mx0 = fmaxf(mx0, fmaxf(s[4*j], s[4*j+1])); mx1 = fmaxf(mx1, fmaxf(s[4*j+2], s[4*j+3]));
    mx0b = fmaxf(mx0b, fmaxf(s[4*j+4], s[4*j+5])); mx1b = fmaxf(mx1b, fmaxf(s[4*j+6], s[4*j+7]));
  }
  mx0 = fmaxf(mx0, mx0b); mx1 = fmaxf(mx1, mx1b);
  mx0 = fmaxf(mx0, __shfl_xor_sync(0xffffffffu, mx0, 1)); mx1 = fmaxf(mx1, __shfl_xor_sync(0xffffffffu, mx1, 1));
  mx0 = fmaxf(mx0, __shfl_xor_sync(0xffffffffu, mx0, 2)); mx1 = fmaxf(mx1, __shfl_xor_sync(0xffffffffu, mx1, 2));
  mx0 *= SCALE_LOG2E; mx1 *= SCALE_LOG2E;
}
__device__ __forceinline__ void exp_tile(const float (&s)[32], uint32_t (&p)[4][4], float nm0, float nm1, float& a0, float& a1) {
#pragma unroll
  for (int k = 0; k < 4; k++) {
#pragma unroll
    for (int h = 0; h < 2; h++) {
      float e0 = ex2(fmaf(s[8*k+4*h],   SCALE_LOG2E, nm0)), e1 = ex2(fmaf(s[8*k+4*h+1], SCALE_LOG2E, nm0));
      float e2 = ex2(fmaf(s[8*k+4*h+2], SCALE_LOG2E, nm1)), e3 = ex2(fmaf(s[8*k+4*h+3], SCALE_LOG2E, nm1));
      if (k == 0 && h == 0) { a0 = e0; a1 = e2; } else { a0 += e0; a1 += e2; }
      a0 += e1; a1 += e3;
      p[k][2*h] = pack_bf16(e0, e1); p[k][2*h+1] = pack_bf16(e2, e3);
    }
  }
}
__device__ __forceinline__ void fence_p(uint32_t (&p)[4][4]) {
#pragma unroll
  for (int k = 0; k < 4; k++)
#pragma unroll
    for (int i = 0; i < 4; i++) asm volatile("" : "+r"(p[k][i]) :: "memory");
}
template<int HALF> __device__ __forceinline__ void issue_qk(float (&s)[32], const uint32_t (&q)[8][4], uint32_t sb) {
  uint64_t d0 = make_desc(sb + HALF * 8192, 16, 1024);
#pragma unroll
  for (int k = 0; k < 8; k++) wgmma_rs_n64<0>(s, q[k], d0 + (((k >> 2) * 16384 + (k & 3) * 32) >> 4), k > 0);
}
template<int HALF> __device__ __forceinline__ void issue_pv(float (&o)[64], const uint32_t (&p)[4][4], uint32_t sb, int acc_first) {
  uint64_t d0 = make_desc(sb + HALF * 8192, 16384, 1024);
#pragma unroll
  for (int k = 0; k < 4; k++) wgmma_rs_n128<1>(o, p[k], d0 + ((k * 2048) >> 4), k > 0 ? 1 : acc_first);
}
__device__ __forceinline__ void softmax_step(float (&s)[32], float (&s_other)[32], uint32_t (&p)[4][4], uint32_t (&p_other)[4][4], float (&o)[64],
                                             float& nm0, float& nm1, float (&l)[2]) {
  float a0, a1;
  exp_tile(s, p, nm0, nm1, a0, a1);
  const bool trip = __any_sync(0xffffffffu, !(fmaxf(a0, a1) <= LAZY_SUM));
  float sc0 = 1.f, sc1 = 1.f;
  if (trip) {
    float mx0, mx1; row_max(s, mx0, mx1);
    float n0 = fminf(nm0, -mx0), n1 = fminf(nm1, -mx1);
    sc0 = ex2(n0 - nm0); sc1 = ex2(n1 - nm1);
    nm0 = n0; nm1 = n1; l[0] *= sc0; l[1] *= sc1;
    exp_tile(s, p, nm0, nm1, a0, a1);
  }
  wgmma_wait<0>(); fence_regs(o); fence_regs(s_other); fence_p(p_other);
  if (trip) {
#pragma unroll
    for (int i = 0; i < 16; i++) { o[4*i] *= sc0; o[4*i+1] *= sc0; o[4*i+2] *= sc1; o[4*i+3] *= sc1; }
  }
  l[0] += a0; l[1] += a1;
}
__device__ __forceinline__ void to_afrag(const float (&s)[64], uint32_t (&p)[8][4]) {
#pragma unroll
  for (int k = 0; k < 8; k++) {
    p[k][0] = pack_bf16(s[8*k], s[8*k+1]); p[k][1] = pack_bf16(s[8*k+2], s[8*k+3]);
    p[k][2] = pack_bf16(s[8*k+4], s[8*k+5]); p[k][3] = pack_bf16(s[8*k+6], s[8*k+7]);
  }
}

template<int TA>
__device__ __forceinline__ void gemm_consume(float (&acc)[80], Ring& r, int nchunks, uint32_t base, uint32_t full, uint32_t empty, int wg, int lane PROF_ARGS) {
  uint32_t prev = 0;
  PROF(10);
#pragma unroll 1
  for (int c = 0; c < nchunks; c++) {
    mbar_wait(full + 8 * r.stage, r.phase);
    PROF(1);
    const uint32_t sp = base + r.stage * STAGE;
    const uint64_t da = make_desc(sp + wg * 8192, 16, 1024), db = make_desc64(sp + 16384, 2048, 512);
    wgmma_fence();
#pragma unroll
    for (int k = 0; k < 4; k++)
      wgmma_ss_n160<TA, 1>(acc, da + (((TA ? 2048 : 32) * k) >> 4), db + (((k >> 1) * 10240 + (k & 1) * 1024) >> 4), (c > 0 || k > 0) ? 1 : 0);
    wgmma_commit();
    if (c > 0) { wgmma_wait<1>(); release_stage(prev, lane); }
    prev = empty + 8 * r.stage;
    r.advance();
  }
  wgmma_wait<0>(); fence_regs(acc);
  release_stage(prev, lane);
}
template<bool ADD>
__device__ __forceinline__ void stage_tile(const uint32_t (&t)[40], Ring& r, uint32_t base, uint32_t full, uint32_t staged, int wg, int warp, int lane) {
  if (wg == 1) r.advance();
  mbar_wait(full + 8 * r.stage, r.phase);
  const int mrow = warp * 16 + (lane & 7) + ((lane >> 3) & 1) * 8;
  const uint32_t ob = base + r.stage * STAGE + mrow * 64;
#pragma unroll
  for (int k = 0; k < 10; k++) {
    const int chunk = (k & 1) * 2 + (lane >> 4);
    const uint32_t addr = ob + (k >> 1) * 4096 + ((chunk ^ ((mrow >> 1) & 3)) << 4);
    if (ADD) {
      uint32_t x0, x1, x2, x3;
      ldmatrix_x4(addr, x0, x1, x2, x3);
      stmatrix_x4(addr, bf2_add(x0, t[4*k]), bf2_add(x1, t[4*k+1]), bf2_add(x2, t[4*k+2]), bf2_add(x3, t[4*k+3]));
    } else stmatrix_x4(addr, t[4*k], t[4*k+1], t[4*k+2], t[4*k+3]);
  }
  fence_async_smem();
  __syncwarp();
  if (lane == 0) mbar_arrive(staged);
  r.advance();
  if (wg == 0) r.advance();
}
__device__ __forceinline__ float mul_sigmoid(float x, float z2) { return x * rcp_fast(1.f + ex2(-z2)); }
__device__ __forceinline__ void bias_act(uint32_t (&t)[40], const float (&acc)[80], uint32_t b0, uint32_t b1, bool gelu) {
  const float k1 = gelu ? 2.f * 0.7978845608028654f * 1.4426950408889634f : 1.4426950408889634f;
  const float k3 = gelu ? k1 * 0.044715f : 0.f;
#pragma unroll
  for (int j = 0; j < 40; j++) t[j] = bf2_add(pack_bf16(acc[2*j], acc[2*j+1]), (j & 1) ? b1 : b0);
#pragma unroll 1
  for (int it = 0; it < 5; it++) {
    uint32_t u[8];
#pragma unroll
    for (int j = 0; j < 8; j++) {
      const float x0 = bf_lo(t[j]), x1 = bf_hi(t[j]);
      u[j] = pack_bf16(mul_sigmoid(x0, x0 * fmaf(x0 * x0, k3, k1)), mul_sigmoid(x1, x1 * fmaf(x1 * x1, k3, k1)));
    }
#pragma unroll
    for (int j = 0; j < 32; j++) t[j] = t[j + 8];
#pragma unroll
    for (int j = 0; j < 8; j++) t[32 + j] = u[j];
  }
}

__global__ void __cluster_dims__(2, 1, 1) __launch_bounds__(384, 1) fused_kernel(const __grid_constant__ Params P) {
  extern __shared__ char smem_raw[];
  uint32_t lnv[20];
  if (blockIdx.x < 128 && threadIdx.x < 256) {
    const uint4* src = (const uint4*)(P.x + (blockIdx.x * 16 + (threadIdx.x >> 4)) * DM) + (threadIdx.x & 15);
#pragma unroll
    for (int i = 0; i < 5; i++) { const uint4 t = __ldg(src + 16 * i); lnv[4*i] = t.x; lnv[4*i+1] = t.y; lnv[4*i+2] = t.z; lnv[4*i+3] = t.w; }
  }
  const uint32_t base = (smem_u32(smem_raw) + 1023) & ~1023u;
  const uint32_t full = base + NST * STAGE, empty = full + 8 * NST, staged = empty + 8 * NST;
  const int wg = __shfl_sync(0xffffffffu, threadIdx.x / 128, 0);
  const int lane = threadIdx.x & 31;
  const uint32_t rank = cluster_ctarank();
  const int cluster_id = blockIdx.x >> 1;
  if (threadIdx.x == 256) {
    for (int i = 0; i < NST; i++) { mbar_init(full + 8 * i, 1); mbar_init(empty + 8 * i, 16); }
    mbar_init(staged, 8);
    asm volatile("fence.mbarrier_init.release.cluster;" ::: "memory");
  }
  __syncwarp();
  cluster_arrive_relaxed();
  if (wg == 2) {
    asm volatile("setmaxnreg.dec.sync.aligned.u32 " PREGS ";");
    const int pw = __shfl_sync(0xffffffffu, (threadIdx.x >> 5) & 3, 0);
    if (pw == 0) {
      if (lane < 13) prefetch_map(&P.xn + lane);
      {
        const uint32_t w = P.sched[cluster_id][0];
        const int a = (w >> 3) & 31;
        if ((w & 7) == T_ATT) {
          if (lane < 10) tma_prefetch_2d(&P.wq, a * 128 + rank * 64, lane * 64);
          else if (lane < 13) tma_prefetch_2d(lane == 12 ? &P.v : &P.k, rank * 64, a * 2048 + (lane == 11) * 128);
        } else if (lane < 16) tma_prefetch_2d(&P.w1, a * 256 + rank * 128 + (lane & 1) * 64, (lane >> 1) * 64);
      }
      uint64_t pol_stream;
      asm volatile("createpolicy.fractional.L2::evict_first.b64 %0, 1.0;" : "=l"(pol_stream));
      cluster_wait();
      Ring r{0, 1};
      uint32_t ln_mask = 0;
#pragma unroll 1
      for (int it = 0; it < MAXI; it++) {
        const uint32_t w = P.sched[cluster_id][it];
        const int type = w & 7, a = (w >> 3) & 31, b = (w >> 8) & 7, c0 = (w >> 11) & 127, c1 = (w >> 18) & 127, e = (w >> 25) & 3;
        if (type == T_END) break;
        int nstaging = 2;
        const int m0 = a * 256 + rank * 128;
        if (type == T_ATT) {
          const int row0 = b * 256 + rank * 128;
          wait_flags(ln_mask, b * 2 + rank, &g_cnt[C_XN], 16, 8, lane);
#pragma unroll 1
          for (int c = 0; c < 10; c++) {
            mbar_wait(empty + 8 * r.stage, r.phase);
            const uint32_t fb = full + 8 * r.stage, sp = base + r.stage * STAGE;
            if (elect_one()) {
              mbar_expect_tx(fb, 32768);
              tma_load_2d(sp, &P.xn, c * 64, row0, fb);
              tma_load_2d_mc(sp + 16384 + rank * 8192, &P.wq, a * 128 + rank * 64, c * 64, fb, 3);
            }
            r.advance();
          }
#pragma unroll 1
          for (int j = 0; j < 32; j++) {
            mbar_wait(empty + 8 * r.stage, r.phase);
            const uint32_t fb = full + 8 * r.stage, sp = base + r.stage * STAGE;
            const bool isk = (j == 0) || ((j & 1) && j < 31);
            const int blk = isk ? (j + 1) / 2 : (j == 31 ? 15 : j / 2 - 1);
            const CUtensorMap* m = isk ? &P.k : &P.v;
            if (elect_one()) {
              mbar_expect_tx(fb, 32768);
              tma_load_2d_mc_hint(sp + rank * 16384, m, rank * 64, a * 2048 + blk * 128, fb, 3, pol_stream);
              if (it == PF_ITEM && blockIdx.x < 128) {
                bulk_prefetch((const char*)P.pw2 + (blockIdx.x * 32 + j) * (SEQ * FF * 2 / 4096), SEQ * FF * 2 / 4096);
                bulk_prefetch((const char*)P.pwo + (blockIdx.x * 32 + j) * (NH * DH * DM * 2 / 4096), NH * DH * DM * 2 / 4096);
              }
            }
            r.advance();
          }
          nstaging = 1;
        } else {
          uint32_t mask = 0;
          if (type == T_MLP1 || type == T_OWN) {
            const CUtensorMap* ma = type == T_MLP1 ? &P.w1 : &P.w2;
            const CUtensorMap* mb = type == T_MLP1 ? &P.h : &P.ut;
            const int n = type == T_MLP1 ? 32 : 27;
            if (type == T_MLP1) { wait_flags(mask, 0, &g_cnt[C_H], 1, 128, lane); mask = ~0u; }
#pragma unroll 1
            for (int c = 0; c < n; c++) {
              wait_flags(mask, c >> 2, &g_cnt[C_U + b * 8], 7, 2, lane);
              mbar_wait(empty + 8 * r.stage, r.phase);
              const uint32_t fb = full + 8 * r.stage, sp = base + r.stage * STAGE;
              if (elect_one()) {
                mbar_expect_tx(fb, STAGE);
                tma_load_2d(sp, ma, m0, c * 64, fb);
                tma_load_2d(sp + 8192, ma, m0 + 64, c * 64, fb);
                tma_load_3d_mc(sp + 16384 + rank * 10240, mb, 0, c * 64 + rank * 32, b * 5, fb, 3);
              }
              r.advance();
            }
          }
          if (type == T_PART || type == T_OWN) {
            mask = 0;
#pragma unroll 1
            for (int c = c0; c < c1; c++) {
              wait_flags(mask, c >> 1, &g_cnt[C_O + (a * 2 + rank) * 32], 32, 1, lane);
              mbar_wait(empty + 8 * r.stage, r.phase);
              const uint32_t fb = full + 8 * r.stage, sp = base + r.stage * STAGE;
              if (elect_one()) {
                mbar_expect_tx(fb, STAGE);
                tma_load_2d(sp, &P.o, c * 64, m0, fb);
                tma_load_3d_mc(sp + 16384 + rank * 10240, &P.wo, 0, c * 64 + rank * 32, b * 5, fb, 3);
              }
              r.advance();
            }
          }
          if (type == T_PART) nstaging = 0;
          if (type == T_OWN) {
            mask = 0;
            const int slot0 = ((a * 4 + b) * 2 + rank) * 3;
#pragma unroll 1
            for (int q = 0; q < 3 * e; q++) {
              const int part = q / 3, pc = q % 3;
              wait_flags(mask, part, &g_cnt[C_PART + slot0], 3, 2, lane);
              mbar_wait(empty + 8 * r.stage, r.phase);
              const uint32_t fb = full + 8 * r.stage, bytes = pc < 2 ? PART_PIECE : 6 * 4096;
              if (elect_one()) {
                mbar_expect_tx(fb, bytes);
                bulk_load(base + r.stage * STAGE, (const char*)(g_part + (slot0 + part) * 20 * 256) + pc * PART_PIECE, bytes, fb);
              }
              r.advance();
            }
          }
        }
#pragma unroll 1
        for (int q = 0; q < nstaging; q++) {
          mbar_wait(empty + 8 * r.stage, r.phase);
          if (elect_one()) {
            if (type == T_OWN) {
              mbar_expect_tx(full + 8 * r.stage, 20480);
              tma_load_3d(base + r.stage * STAGE, &P.x_ld, 0, m0 + q * 64, b * 5, full + 8 * r.stage);
            } else mbar_arrive(full + 8 * r.stage);
          }
          r.advance();
        }
      }
    } else {
      cluster_wait();
      if (pw == 1 && lane == 0) {
        Ring r{0, 0};
        uint32_t sph = 0;
        _Pragma("unroll 1") for (int it = 0; it < MAXI; it++) {
          const uint32_t w = P.sched[cluster_id][it];
          const int type = w & 7, a = (w >> 3) & 31, b = (w >> 8) & 7, c0 = (w >> 11) & 127, c1 = (w >> 18) & 127, e = (w >> 25) & 3;
          if (type == T_END) break;
          if (type == T_PART) { r.skip(c1 - c0); continue; }
          r.skip(type == T_ATT ? 42 : type == T_MLP1 ? 32 : 27 + c1 - c0 + 3 * e);
          const uint32_t s0 = r.stage; r.skip(1);
          const uint32_t s1 = r.stage;
          mbar_wait(staged, sph); sph ^= 1;
          uint32_t* flag = nullptr;
          if (type == T_ATT) {
            const int row0 = b * 256 + rank * 128;
            tma_store_2d(&P.o, base + s0 * STAGE, a * 128, row0);
            tma_store_2d(&P.o, base + s0 * STAGE + 16384, a * 128 + 64, row0);
            flag = &g_cnt[C_O + (b * 2 + rank) * 32 + a];
          } else {
            const CUtensorMap* m = type == T_MLP1 ? &P.ut_st : &P.out_st;
            const int m0 = a * 256 + rank * 128;
            tma_store_3d(m, base + s0 * STAGE, 0, m0, b * 5);
            tma_store_3d(m, base + s1 * STAGE, 0, m0 + 64, b * 5);
            r.skip(1);
            if (type == T_MLP1) flag = &g_cnt[C_U + b * 8 + a];
          }
          bulk_commit();
          bulk_wait_read<0>();
          mbar_arrive_cluster_n(empty + 8 * s0, 0, 8); mbar_arrive_cluster_n(empty + 8 * s0, 1, 8);
          if (type != T_ATT) { mbar_arrive_cluster_n(empty + 8 * s1, 0, 8); mbar_arrive_cluster_n(empty + 8 * s1, 1, 8); }
          bulk_wait<0>();
          fence_async_global();
          if (flag) red_release(flag, 1);
        }
      }
    }
    __syncwarp();
    cluster_arrive(); cluster_wait();
  } else {
    asm volatile("setmaxnreg.inc.sync.aligned.u32 " CREGS ";");
    const int warp = (threadIdx.x >> 5) & 3;
    const int tid = threadIdx.x & 127;
    ITEMCLK(9);
    if (blockIdx.x < 128) {
#pragma unroll 1
      for (int pass = 0; pass < 2; pass++) {
        ln_row(lnv);
        uint4* dst = (uint4*)((pass ? g_h : g_xn) + (blockIdx.x * 16 + (threadIdx.x >> 4)) * DM) + (threadIdx.x & 15);
#pragma unroll
        for (int i = 0; i < 5; i++) dst[16 * i] = make_uint4(lnv[4*i], lnv[4*i+1], lnv[4*i+2], lnv[4*i+3]);
        bar_sync(1, 256);
        if (threadIdx.x == pass * 128) red_release(&g_cnt[pass ? C_H : C_XN + (blockIdx.x >> 3)], 1);
      }
    }
    cluster_wait();
    Ring r{0, 0};
    int cn = 0; (void)cn;
#pragma unroll 1
    for (int it = 0; it < MAXI; it++) {
      const uint32_t w = P.sched[cluster_id][it];
      const int type = w & 7, a = (w >> 3) & 31, b = (w >> 8) & 7;
      if (type == T_END) break;
      ITEMCLK(it);
      if (type == T_ATT) {
        float sa[32], sb[32], o[64];
        uint32_t q[8][4], pa[4][4], pb[4][4];
        zero_regs(sa); zero_regs(sb); zero_regs(o);
#pragma unroll
        for (int i = 0; i < 16; i++) { pa[i >> 2][i & 3] = 0; pb[i >> 2][i & 3] = 0; }
        PROF(10); CLKS();
        {
          uint32_t prev = 0;
#pragma unroll 1
          for (int c = 0; c < 10; c++) {
            mbar_wait(full + 8 * r.stage, r.phase);
            const uint32_t sp = base + r.stage * STAGE;
            const uint64_t da = make_desc(sp + wg * 8192, 16, 1024), db = make_desc(sp + 16384, 8192, 1024);
            wgmma_fence();
#pragma unroll
            for (int k = 0; k < 4; k++) wgmma_ss_n128<0, 1>(o, da + ((k * 32) >> 4), db + ((k * 2048) >> 4), (c > 0 || k > 0) ? 1 : 0);
            wgmma_commit();
            if (c > 0) { wgmma_wait<1>(); release_stage(prev, lane); }
            prev = empty + 8 * r.stage;
            r.advance();
          }
          wgmma_wait<0>(); fence_regs(o);
          release_stage(prev, lane);
          to_afrag(o, q);
        }
        float l[2], nm0, nm1;
        PROF(11); ITEMCLK(16 + it);
        mbar_wait(full + 8 * r.stage, r.phase);
        uint32_t krel = empty + 8 * r.stage, vrel = 0;
        wgmma_fence();
        issue_qk<0>(sa, q, base + r.stage * STAGE);
        wgmma_commit();
        issue_qk<1>(sb, q, base + r.stage * STAGE);
        wgmma_commit();
        r.advance();
        uint32_t kst = r.stage; mbar_wait(full + 8 * r.stage, r.phase); r.advance();
        uint32_t vst = r.stage; mbar_wait(full + 8 * r.stage, r.phase); r.advance();
        wgmma_wait<1>(); fence_regs(sa);
        row_max(sa, nm0, nm1); nm0 = -nm0; nm1 = -nm1;
        l[0] = 0.f; l[1] = 0.f;
#pragma unroll 1
        for (int j = 0; j < 15; j++) {
          PROF(5); CLKS();
          softmax_step(sa, sb, pa, pb, o, nm0, nm1, l);
          PROF(0);
          release_stage(krel, lane);
          if (j > 0) release_stage(vrel, lane);
          wgmma_fence();
          issue_qk<0>(sa, q, base + kst * STAGE);
          issue_pv<0>(o, pa, base + vst * STAGE, j > 0);
          wgmma_commit();
          const uint32_t nst = r.stage; mbar_wait(full + 8 * r.stage, r.phase); r.advance();
          PROF(1);
          softmax_step(sb, sa, pb, pa, o, nm0, nm1, l);
          PROF(2);
          wgmma_fence();
          issue_qk<1>(sb, q, base + kst * STAGE);
          krel = empty + 8 * kst; vrel = empty + 8 * vst;
          const uint32_t vcur = vst;
          kst = nst; vst = nst;
          if (j < 14) { vst = r.stage; mbar_wait(full + 8 * r.stage, r.phase); r.advance(); }
          issue_pv<1>(o, pb, base + vcur * STAGE, 1);
          wgmma_commit();
          PROF(3);
        }
        PROF(12);
        softmax_step(sa, sb, pa, pb, o, nm0, nm1, l);
        release_stage(krel, lane);
        release_stage(vrel, lane);
        wgmma_fence();
        issue_pv<0>(o, pa, base + vst * STAGE, 1);
        wgmma_commit();
        mbar_wait(full + 8 * r.stage, r.phase);
        softmax_step(sb, sa, pb, pa, o, nm0, nm1, l);
        wgmma_fence();
        issue_pv<1>(o, pb, base + vst * STAGE, 1);
        wgmma_commit();
        l[0] += __shfl_xor_sync(0xffffffffu, l[0], 1); l[1] += __shfl_xor_sync(0xffffffffu, l[1], 1);
        l[0] += __shfl_xor_sync(0xffffffffu, l[0], 2); l[1] += __shfl_xor_sync(0xffffffffu, l[1], 2);
        const float i0 = rcp_fast(l[0]), i1 = rcp_fast(l[1]);
        wgmma_wait<0>(); fence_regs(o);
        release_stage(empty + 8 * vst, lane);
        PROF(13);
        const int mrow = wg * 64 + warp * 16 + (lane & 7) + ((lane >> 3) & 1) * 8;
        const uint32_t ob = base + r.stage * STAGE + mrow * 128;
#pragma unroll
        for (int k = 0; k < 8; k++) {
          const uint32_t r0 = pack_bf16(o[8*k] * i0, o[8*k+1] * i0), r1 = pack_bf16(o[8*k+2] * i1, o[8*k+3] * i1);
          const uint32_t r2 = pack_bf16(o[8*k+4] * i0, o[8*k+5] * i0), r3 = pack_bf16(o[8*k+6] * i1, o[8*k+7] * i1);
          const int chunk = (k & 3) * 2 + (lane >> 4);
          stmatrix_x4(ob + (k >> 2) * 16384 + ((chunk ^ (mrow & 7)) << 4), r0, r1, r2, r3);
        }
        fence_async_smem();
        __syncwarp();
        if (lane == 0) mbar_arrive(staged);
        r.advance();
        PROF(14);
      } else {
        const int c0 = (w >> 11) & 127, c1 = (w >> 18) & 127, e = (w >> 25) & 3;
        float acc[80];
        uint32_t t[40];
        zero_regs(acc);
#pragma unroll
        for (int j = 0; j < 40; j++) t[j] = 0;
        if (type != T_PART) {
          const int row = min(a * 256 + rank * 128 + wg * 64 + warp * 16 + (lane >> 2), (type == T_MLP1 ? FF : SEQ) - 9);
          const unsigned short* bias = (const unsigned short*)(type == T_MLP1 ? P.b1 : P.b2);
          prefetch_l1(bias + row);
          gemm_consume<1>(acc, r, type == T_MLP1 ? 32 : 27, base, full, empty, wg, lane PROF_PASS);
          ITEMCLK(16 + it);
          const uint32_t b0 = bias[row] * 0x10001u, b1 = bias[row + 8] * 0x10001u;
          bias_act(t, acc, b0, b1, type == T_MLP1);
        }
        if (type == T_MLP1) {
          stage_tile<false>(t, r, base, full, staged, wg, warp, lane);
        } else {
          gemm_consume<0>(acc, r, c1 - c0, base, full, empty, wg, lane PROF_PASS);
          ITEMCLK(24 + it);
          if (type == T_PART) {
            const int slot = ((a * 4 + b) * 2 + rank) * 3 + e;
            float4* dst = g_part + slot * 20 * 256 + wg * 128 + tid;
#pragma unroll
            for (int j = 0; j < 20; j++) dst[j * 256] = make_float4(acc[4*j], acc[4*j+1], acc[4*j+2], acc[4*j+3]);
            bar_sync(3 + wg, 128);
            if (tid == 0) red_release(&g_cnt[C_PART + slot], 1);
          } else {
#pragma unroll 1
            for (int q = 0; q < e; q++) {
#pragma unroll
              for (int pc = 0; pc < 3; pc++) {
                mbar_wait(full + 8 * r.stage, r.phase);
                const uint32_t sp = base + r.stage * STAGE + (wg * 128 + tid) * 16;
#pragma unroll
                for (int j = 0; j < (pc < 2 ? 7 : 6); j++) {
                  float4 v;
                  asm volatile("ld.shared.v4.f32 {%0, %1, %2, %3}, [%4];" : "=f"(v.x), "=f"(v.y), "=f"(v.z), "=f"(v.w) : "r"(sp + j * 4096) : "memory");
                  const int jj = pc * 7 + j;
                  acc[4*jj] += v.x; acc[4*jj+1] += v.y; acc[4*jj+2] += v.z; acc[4*jj+3] += v.w;
                }
                __syncwarp();
                release_stage(empty + 8 * r.stage, lane);
                r.advance();
              }
            }
#pragma unroll
            for (int j = 0; j < 40; j++) t[j] = bf2_mul(pack_bf16(acc[2*j], acc[2*j+1]), t[j]);
            PROF(11);
            stage_tile<true>(t, r, base, full, staged, wg, warp, lane);
            PROF(12);
          }
        }
      }
    }
    ITEMCLK(MAXI);
    __syncwarp();
    cluster_arrive(); cluster_wait();
    if (threadIdx.x < 32) {
      uint32_t t = 0;
      if (lane == 0) { __threadfence(); t = atomicAdd(&g_cnt[C_DONE], 1); }
      t = __shfl_sync(0xffffffffu, t, 0);
      if (t == gridDim.x - 1) {
        __threadfence();
        for (int i = lane; i < C_TOTAL; i += 32) g_cnt[i] = 0;
      }
    }
  }
}

typedef CUresult (*EncodeFn)(CUtensorMap*, CUtensorMapDataType, cuuint32_t, void*, const cuuint64_t*, const cuuint64_t*, const cuuint32_t*, const cuuint32_t*,
                             CUtensorMapInterleave, CUtensorMapSwizzle, CUtensorMapL2promotion, CUtensorMapFloatOOBfill);
static void make_map(EncodeFn fn, CUtensorMap* m, const void* ptr, uint64_t inner, uint64_t outer, uint32_t box_inner, uint32_t box_outer) {
  cuuint64_t dims[2] = {inner, outer}; cuuint64_t strides[1] = {inner * 2}; cuuint32_t box[2] = {box_inner, box_outer}; cuuint32_t es[2] = {1, 1};
  fn(m, CU_TENSOR_MAP_DATA_TYPE_BFLOAT16, 2, (void*)ptr, dims, strides, box, es, CU_TENSOR_MAP_INTERLEAVE_NONE, CU_TENSOR_MAP_SWIZZLE_128B,
     CU_TENSOR_MAP_L2_PROMOTION_L2_256B, CU_TENSOR_MAP_FLOAT_OOB_FILL_NONE);
}
static void make_map_b(EncodeFn fn, CUtensorMap* m, const void* ptr, uint64_t rows, uint32_t box_rows = 32) {
  cuuint64_t dims[3] = {32, rows, DM / 32}; cuuint64_t strides[2] = {DM * 2, 64}; cuuint32_t box[3] = {32, box_rows, 5}; cuuint32_t es[3] = {1, 1, 1};
  fn(m, CU_TENSOR_MAP_DATA_TYPE_BFLOAT16, 3, (void*)ptr, dims, strides, box, es, CU_TENSOR_MAP_INTERLEAVE_NONE, CU_TENSOR_MAP_SWIZZLE_64B,
     CU_TENSOR_MAP_L2_PROMOTION_L2_256B, CU_TENSOR_MAP_FLOAT_OOB_FILL_NONE);
}
static inline uint32_t item(int type, int a, int b, int c0 = 0, int c1 = 0, int e = 0) { return type | a << 3 | b << 8 | c0 << 11 | c1 << 18 | e << 25; }
static void build_schedule(uint32_t (&sched)[NCL][MAXI]) {
  int n[NCL];
  for (int c = 0; c < NCL; c++) { n[c] = 0; for (int i = 0; i < MAXI; i++) sched[c][i] = T_END; }
  int m1 = 0;
  for (int c = 54; c < 66; c++, m1++) sched[c][n[c]++] = item(T_MLP1, m1 >> 2, m1 & 3);
  for (int i = 0; i < 2; i++) for (int c = 58; c < 66; c++, m1++) sched[c][n[c]++] = item(T_MLP1, m1 >> 2, m1 & 3);
  const int order[11][2] = {{0, 54}, {54, 58}, {0, 54}, {54, 58}, {58, 66}, {0, 54}, {54, 58}, {58, 66}, {0, 54}, {54, 58}, {58, 66}};
  int u = 0;
  for (int g = 0; g < 11; g++) for (int c = order[g][0]; c < order[g][1]; c++, u++) sched[c][n[c]++] = item(T_ATT, u >> 3, u & 7);
  const int d = PART_D, h = d / 2;
  for (int t = 0; t < 32; t++) {
    const int g = t / 3, k = t % 3, ca = 32 + 2 * g, cb = ca + 1;
    int np = 1;
    if (g == 10) sched[ca + k][n[ca + k]++] = item(T_PART, t >> 2, t & 3, 0, d, 0);
    else if (k == 0) { np = 2; sched[ca][n[ca]++] = item(T_PART, t >> 2, t & 3, 0, h, 0); sched[cb][n[cb]++] = item(T_PART, t >> 2, t & 3, h, d, 1); }
    else { const int c = k == 1 ? ca : cb; sched[c][n[c]++] = item(T_PART, t >> 2, t & 3, 0, d, 0); }
    sched[t][n[t]++] = item(T_OWN, t >> 2, t & 3, d, 64, np);
  }
}
extern "C" void kernel_launch(void* const* d_in, const int* in_sizes, int n_in, void* d_out, int out_size) {
  void* fnp = nullptr; cudaDriverEntryPointQueryResult qr;
  cudaGetDriverEntryPoint("cuTensorMapEncodeTiled", &fnp, cudaEnableDefault, &qr);
  EncodeFn fn = (EncodeFn)fnp;
  void *xn, *h, *o, *ut;
  cudaGetSymbolAddress(&xn, g_xn); cudaGetSymbolAddress(&h, g_h); cudaGetSymbolAddress(&o, g_o); cudaGetSymbolAddress(&ut, g_ut);
  Params p;
  make_map(fn, &p.xn, xn, DM, SEQ, 64, 128);
  make_map(fn, &p.wq, d_in[3], NH * DH, DM, 64, 64);
  make_map(fn, &p.k, d_in[1], DH, NH * SEQ, 64, 128);
  make_map(fn, &p.v, d_in[2], DH, NH * SEQ, 64, 128);
  make_map(fn, &p.o, o, NH * DH, SEQ, 64, 128);
  make_map(fn, &p.w1, d_in[6], FF, SEQ, 64, 64);
  make_map(fn, &p.w2, d_in[8], SEQ, FF, 64, 64);
  make_map_b(fn, &p.wo, d_in[4], NH * DH);
  make_map_b(fn, &p.h, h, SEQ);
  make_map_b(fn, &p.ut, ut, FF);
  make_map_b(fn, &p.ut_st, ut, FF, 64);
  make_map_b(fn, &p.out_st, d_out, SEQ, 64);
  make_map_b(fn, &p.x_ld, d_in[0], SEQ, 64);
  p.x = (const bf16*)d_in[0]; p.b1 = (const bf16*)d_in[7]; p.b2 = (const bf16*)d_in[9];
  p.pw1 = (const bf16*)d_in[6]; p.pw2 = (const bf16*)d_in[8]; p.pwo = (const bf16*)d_in[4];
  build_schedule(p.sched);
  cudaFuncSetAttribute(fused_kernel, cudaFuncAttributeMaxDynamicSharedMemorySize, SMEM_BYTES);
  fused_kernel<<<2 * NCL, 384, SMEM_BYTES, cudaStreamPerThread>>>(p);
}
```

```cpp
#include <cuda_runtime.h>
#include <cuda_bf16.h>
#include <cuda.h>
#include <stdint.h>

typedef __nv_bfloat16 bf16;
constexpr int SEQ = 2048, DM = 640, NH = 32, DH = 128, FF = 1728;

__device__ __align__(128) bf16 g_xn[SEQ * DM];
__device__ __align__(128) bf16 g_h[SEQ * DM];
__device__ __align__(128) bf16 g_o[SEQ * NH * DH];
__device__ __align__(128) bf16 g_ut[FF * DM];
__device__ __align__(128) uint4 g_part[32 * 2 * 3 * 2 * 1280];
constexpr int C_XN = 0, C_DONE = 16, C_TICKET = 17, C_U = 32, C_PART = 64, C_O = 256, C_H = 768, C_TOTAL = 768 + 32;
__device__ __align__(16) uint32_t g_cnt[C_TOTAL];

__device__ __forceinline__ uint32_t smem_u32(const void* p) { return (uint32_t)__cvta_generic_to_shared(p); }
__device__ __forceinline__ void mbar_init(uint32_t bar, uint32_t cnt) { asm volatile("mbarrier.init.shared::cta.b64 [%0], %1;" :: "r"(bar), "r"(cnt)); }
__device__ __forceinline__ void mbar_expect_tx(uint32_t bar, uint32_t bytes) { asm volatile("mbarrier.arrive.expect_tx.shared::cta.b64 _, [%0], %1;" :: "r"(bar), "r"(bytes) : "memory"); }
__device__ __forceinline__ void mbar_arrive(uint32_t bar) { asm volatile("mbarrier.arrive.shared::cta.b64 _, [%0];" :: "r"(bar) : "memory"); }
__device__ __forceinline__ void mbar_arrive_cluster(uint32_t bar, uint32_t cta) {
  asm volatile("{\n.reg .b32 ra;\nmapa.shared::cluster.u32 ra, %0, %1;\nmbarrier.arrive.shared::cluster.b64 _, [ra];\n}" :: "r"(bar), "r"(cta) : "memory"); }
__device__ __forceinline__ bool mbar_try_wait(uint32_t bar, uint32_t parity) {
  uint32_t ok;
  asm volatile("{\n.reg .pred p;\nmbarrier.try_wait.parity.shared::cta.b64 p, [%1], %2;\nselp.b32 %0, 1, 0, p;\n}" : "=r"(ok) : "r"(bar), "r"(parity) : "memory");
  return ok; }
__device__ __forceinline__ void mbar_wait(uint32_t bar, uint32_t parity) {
  asm volatile("{\n.reg .pred p;\n.reg .u32 n;\nmov.u32 n, 0;\n"
               "LAB_WAIT:\n"
               "mbarrier.try_wait.parity.shared::cta.b64 p, [%0], %1;\n"
               "@p bra LAB_DONE;\n"
               "add.u32 n, n, 1;\n"
               "setp.lt.u32 p, n, 0x400000;\n"
               "@p bra LAB_WAIT;\n"
               "trap;\n"
               "LAB_DONE:\n}" :: "r"(bar), "r"(parity) : "memory"); }
__device__ __forceinline__ void tma_load_2d(uint32_t dst, const CUtensorMap* map, int c0, int c1, uint32_t bar) {
  asm volatile("cp.async.bulk.tensor.2d.shared::cluster.global.mbarrier::complete_tx::bytes [%0], [%1, {%3, %4}], [%2];"
    :: "r"(dst), "l"(map), "r"(bar), "r"(c0), "r"(c1) : "memory"); }
__device__ __forceinline__ void tma_load_2d_mc(uint32_t dst, const CUtensorMap* map, int c0, int c1, uint32_t bar, uint16_t mask) {
  asm volatile("cp.async.bulk.tensor.2d.shared::cluster.global.mbarrier::complete_tx::bytes.multicast::cluster [%0], [%1, {%3, %4}], [%2], %5;"
    :: "r"(dst), "l"(map), "r"(bar), "r"(c0), "r"(c1), "h"(mask) : "memory"); }
__device__ __forceinline__ void bulk_commit() { asm volatile("cp.async.bulk.commit_group;" ::: "memory"); }
template<int N> __device__ __forceinline__ void bulk_wait_read() { asm volatile("cp.async.bulk.wait_group.read %0;" :: "n"(N) : "memory"); }
template<int N> __device__ __forceinline__ void bulk_wait() { asm volatile("cp.async.bulk.wait_group %0;" :: "n"(N) : "memory"); }
__device__ __forceinline__ void fence_async_smem() { asm volatile("fence.proxy.async.shared::cta;" ::: "memory"); }
__device__ __forceinline__ void wgmma_fence() { asm volatile("wgmma.fence.sync.aligned;" ::: "memory"); }
__device__ __forceinline__ void wgmma_commit() { asm volatile("wgmma.commit_group.sync.aligned;" ::: "memory"); }
template<int N> __device__ __forceinline__ void wgmma_wait() { asm volatile("wgmma.wait_group.sync.aligned %0;" :: "n"(N) : "memory"); }
__device__ __forceinline__ uint64_t make_desc(uint32_t addr, uint32_t lbo, uint32_t sbo) {
  return (uint64_t)((addr & 0x3FFFF) >> 4) | ((uint64_t)(lbo >> 4) << 16) | ((uint64_t)(sbo >> 4) << 32) | (1ull << 62); }
__device__ __forceinline__ uint32_t cluster_ctarank() { uint32_t r; asm volatile("mov.u32 %0, %%cluster_ctarank;" : "=r"(r)); return r; }
__device__ __forceinline__ void cluster_wait() { asm volatile("barrier.cluster.wait.acquire.aligned;" ::: "memory"); }
__device__ __forceinline__ void bar_sync(int id, int n) { asm volatile("bar.sync %0, %1;" :: "r"(id), "r"(n) : "memory"); }
__device__ __forceinline__ void bar_arrive(int id, int n) { asm volatile("bar.arrive %0, %1;" :: "r"(id), "r"(n) : "memory"); }
__device__ __forceinline__ float ex2(float x) { float y; asm("ex2.approx.ftz.f32 %0, %1;" : "=f"(y) : "f"(x)); return y; }
__device__ __forceinline__ uint32_t pack_bf16(float lo, float hi) { uint32_t r; asm("cvt.rn.bf16x2.f32 %0, %1, %2;" : "=r"(r) : "f"(hi), "f"(lo)); return r; }
__device__ __forceinline__ float rbf16(float x) { return __bfloat162float(__float2bfloat16(x)); }
__device__ __forceinline__ void stmatrix_x4(uint32_t addr, uint32_t r0, uint32_t r1, uint32_t r2, uint32_t r3) {
  asm volatile("stmatrix.sync.aligned.m8n8.x4.shared.b16 [%0], {%1, %2, %3, %4};" :: "r"(addr), "r"(r0), "r"(r1), "r"(r2), "r"(r3) : "memory"); }
template<int R> __device__ __forceinline__ void fence_regs(float (&a)[R]) {
#pragma unroll
  for (int i = 0; i < R; i++) asm volatile("" : "+f"(a[i]) :: "memory"); }

__device__ __forceinline__ void tma_load_3d_mc(uint32_t dst, const CUtensorMap* map, int c0, int c1, int c2, uint32_t bar, uint16_t mask) {
  asm volatile("cp.async.bulk.tensor.3d.shared::cluster.global.mbarrier::complete_tx::bytes.multicast::cluster [%0], [%1, {%3, %4, %5}], [%2], %6;"
    :: "r"(dst), "l"(map), "r"(bar), "r"(c0), "r"(c1), "r"(c2), "h"(mask) : "memory"); }
__device__ __forceinline__ void bulk_load(uint32_t dst, const void* src, uint32_t bytes, uint32_t bar) {
  asm volatile("cp.async.bulk.shared::cluster.global.mbarrier::complete_tx::bytes [%0], [%1], %2, [%3];" :: "r"(dst), "l"(src), "r"(bytes), "r"(bar) : "memory"); }
__device__ __forceinline__ void fence_async_global() { asm volatile("fence.proxy.async.global;" ::: "memory"); }
__device__ __forceinline__ void cluster_arrive_relaxed() { asm volatile("barrier.cluster.arrive.relaxed.aligned;" ::: "memory"); }
__device__ __forceinline__ void tma_load_3d(uint32_t dst, const CUtensorMap* map, int c0, int c1, int c2, uint32_t bar) {
  asm volatile("cp.async.bulk.tensor.3d.shared::cluster.global.mbarrier::complete_tx::bytes [%0], [%1, {%3, %4, %5}], [%2];"
    :: "r"(dst), "l"(map), "r"(bar), "r"(c0), "r"(c1), "r"(c2) : "memory"); }
__device__ __forceinline__ void ldmatrix_x4(uint32_t addr, uint32_t& r0, uint32_t& r1, uint32_t& r2, uint32_t& r3) {
  asm volatile("ldmatrix.sync.aligned.m8n8.x4.shared.b16 {%0, %1, %2, %3}, [%4];" : "=r"(r0), "=r"(r1), "=r"(r2), "=r"(r3) : "r"(addr) : "memory"); }
__device__ __forceinline__ uint32_t bf2_add(uint32_t a, uint32_t b) { uint32_t r; asm("add.rn.bf16x2 %0, %1, %2;" : "=r"(r) : "r"(a), "r"(b)); return r; }
__device__ __forceinline__ uint32_t bf2_sub(uint32_t a, uint32_t b) { uint32_t r; asm("sub.rn.bf16x2 %0, %1, %2;" : "=r"(r) : "r"(a), "r"(b)); return r; }
__device__ __forceinline__ uint32_t bf2_mul(uint32_t a, uint32_t b) { uint32_t r; asm("mul.rn.bf16x2 %0, %1, %2;" : "=r"(r) : "r"(a), "r"(b)); return r; }
__device__ __forceinline__ float bf_lo(uint32_t v) { return __uint_as_float(v << 16); }
__device__ __forceinline__ float bf_hi(uint32_t v) { return __uint_as_float(v & 0xffff0000u); }
__device__ __forceinline__ float rcp_fast(float x) { float y; asm("rcp.approx.ftz.f32 %0, %1;" : "=f"(y) : "f"(x)); return y; }
__device__ __forceinline__ float sqrt_fast(float x) { float y; asm("sqrt.approx.ftz.f32 %0, %1;" : "=f"(y) : "f"(x)); return y; }
__device__ __forceinline__ uint32_t ld_acquire(const uint32_t* p) { uint32_t v; asm volatile("ld.acquire.gpu.global.u32 %0, [%1];" : "=r"(v) : "l"(p) : "memory"); return v; }
__device__ __forceinline__ void red_release(uint32_t* p, uint32_t v) { asm volatile("red.release.gpu.global.add.u32 [%0], %1;" :: "l"(p), "r"(v) : "memory"); }
__device__ __forceinline__ uint64_t make_desc64(uint32_t addr, uint32_t lbo, uint32_t sbo) {
  return (uint64_t)((addr & 0x3FFFF) >> 4) | ((uint64_t)(lbo >> 4) << 16) | ((uint64_t)(sbo >> 4) << 32) | (2ull << 62); }

template<int R> __device__ __forceinline__ void zero_regs(float (&a)[R]) {
#pragma unroll
  for (int i = 0; i < R; i++) a[i] = 0.f; }

__device__ __forceinline__ void tma_store_3d(const CUtensorMap* map, uint32_t src, int c0, int c1, int c2) {
  asm volatile("cp.async.bulk.tensor.3d.global.shared::cta.bulk_group [%0, {%2, %3, %4}], [%1];" :: "l"(map), "r"(src), "r"(c0), "r"(c1), "r"(c2) : "memory"); }
__device__ __forceinline__ void prefetch_map(const CUtensorMap* map) { asm volatile("prefetch.tensormap [%0];" :: "l"(map) : "memory"); }
__device__ __forceinline__ void mbar_arrive_cluster_n(uint32_t bar, uint32_t cta, uint32_t n) {
  asm volatile("{\n.reg .b32 ra;\nmapa.shared::cluster.u32 ra, %0, %1;\nmbarrier.arrive.shared::cluster.b64 _, [ra], %2;\n}" :: "r"(bar), "r"(cta), "r"(n) : "memory"); }
__device__ __forceinline__ void wait_flags(uint32_t& mask, int bit, const uint32_t* cnt, int n, uint32_t target, int lane) {
  if (mask >> bit & 1) return;
  _Pragma("unroll 1") for (uint32_t spin = 0; spin < 0x200000; spin++) {
    const bool ok = lane < n && ld_acquire(cnt + lane) >= target;
    mask = __ballot_sync(0xffffffffu, ok);
    if (mask >> bit & 1) break;
    __nanosleep(40);
  }
  __syncwarp();
  fence_async_global();
}

__device__ __forceinline__ bool elect_one() {
  uint32_t p; asm volatile("{\n.reg .pred P;\nelect.sync _|P, 0xffffffff;\nselp.b32 %0, 1, 0, P;\n}" : "=r"(p)); return p; }
__device__ __forceinline__ void prefetch_l1(const void* p) { asm volatile("prefetch.global.L1 [%0];" :: "l"(p)); }

__device__ __forceinline__ void bulk_store(void* dst, uint32_t src, uint32_t bytes) {
  asm volatile("cp.async.bulk.global.shared::cta.bulk_group [%0], [%1], %2;" :: "l"(dst), "r"(src), "r"(bytes) : "memory"); }

__device__ __forceinline__ void order_after(uint32_t v, uint32_t scratch) {
  if (v == 0xffffffffu) asm volatile("st.shared.u32 [%0], %0;" :: "r"(scratch) : "memory"); }

__device__ __forceinline__ void tma_prefetch_2d(const CUtensorMap* map, int c0, int c1) {
  asm volatile("cp.async.bulk.prefetch.tensor.2d.L2.global [%0, {%1, %2}];" :: "l"(map), "r"(c0), "r"(c1) : "memory"); }

template<int TB> __device__ __forceinline__ void wgmma_rs_n64(float (&d)[32], const uint32_t (&a)[4], uint64_t db, int scale_d) {
  asm volatile("{\n.reg .pred p;\n"
    "setp.ne.b32 p, %37, 0;\n"
    "wgmma.mma_async.sync.aligned.m64n64k16.f32.bf16.bf16 "
    "{%0, %1, %2, %3, %4, %5, %6, %7, %8, %9, %10, %11, %12, %13, %14, %15, %16, %17, %18, %19, %20, %21, %22, %23, %24, %25, %26, %27, %28, %29, %30, %31}, "
    "{%32, %33, %34, %35}, %36, p, 1, 1, %38;\n}\n"
    : "+f"(d[0]), "+f"(d[1]), "+f"(d[2]), "+f"(d[3]), "+f"(d[4]), "+f"(d[5]), "+f"(d[6]), "+f"(d[7]), "+f"(d[8]), "+f"(d[9]), "+f"(d[10]), "+f"(d[11]), "+f"(d[12]), "+f"(d[13]), "+f"(d[14]), "+f"(d[15]), "+f"(d[16]), "+f"(d[17]), "+f"(d[18]), "+f"(d[19]), "+f"(d[20]), "+f"(d[21]), "+f"(d[22]), "+f"(d[23]), "+f"(d[24]), "+f"(d[25]), "+f"(d[26]), "+f"(d[27]), "+f"(d[28]), "+f"(d[29]), "+f"(d[30]), "+f"(d[31])
    : "r"(a[0]), "r"(a[1]), "r"(a[2]), "r"(a[3]), "l"(db), "r"(scale_d), "n"(TB));
}
template<int TB> __device__ __forceinline__ void wgmma_rs_n128(float (&d)[64], const uint32_t (&a)[4], uint64_t db, int scale_d) {
  asm volatile("{\n.reg .pred p;\n"
    "setp.ne.b32 p, %69, 0;\n"
    "wgmma.mma_async.sync.aligned.m64n128k16.f32.bf16.bf16 "
    "{%0, %1, %2, %3, %4, %5, %6, %7, %8, %9, %10, %11, %12, %13, %14, %15, %16, %17, %18, %19, %20, %21, %22, %23, %24, %25, %26, %27, %28, %29, %30, %31, %32, %33, %34, %35, %36, %37, %38, %39, %40, %41, %42, %43, %44, %45, %46, %47, %48, %49, %50, %51, %52, %53, %54, %55, %56, %57, %58, %59, %60, %61, %62, %63}, "
    "{%64, %65, %66, %67}, %68, p, 1, 1, %70;\n}\n"
    : "+f"(d[0]), "+f"(d[1]), "+f"(d[2]), "+f"(d[3]), "+f"(d[4]), "+f"(d[5]), "+f"(d[6]), "+f"(d[7]), "+f"(d[8]), "+f"(d[9]), "+f"(d[10]), "+f"(d[11]), "+f"(d[12]), "+f"(d[13]), "+f"(d[14]), "+f"(d[15]), "+f"(d[16]), "+f"(d[17]), "+f"(d[18]), "+f"(d[19]), "+f"(d[20]), "+f"(d[21]), "+f"(d[22]), "+f"(d[23]), "+f"(d[24]), "+f"(d[25]), "+f"(d[26]), "+f"(d[27]), "+f"(d[28]), "+f"(d[29]), "+f"(d[30]), "+f"(d[31]), "+f"(d[32]), "+f"(d[33]), "+f"(d[34]), "+f"(d[35]), "+f"(d[36]), "+f"(d[37]), "+f"(d[38]), "+f"(d[39]), "+f"(d[40]), "+f"(d[41]), "+f"(d[42]), "+f"(d[43]), "+f"(d[44]), "+f"(d[45]), "+f"(d[46]), "+f"(d[47]), "+f"(d[48]), "+f"(d[49]), "+f"(d[50]), "+f"(d[51]), "+f"(d[52]), "+f"(d[53]), "+f"(d[54]), "+f"(d[55]), "+f"(d[56]), "+f"(d[57]), "+f"(d[58]), "+f"(d[59]), "+f"(d[60]), "+f"(d[61]), "+f"(d[62]), "+f"(d[63])
    : "r"(a[0]), "r"(a[1]), "r"(a[2]), "r"(a[3]), "l"(db), "r"(scale_d), "n"(TB));
}
template<int TA, int TB> __device__ __forceinline__ void wgmma_ss_n128(float (&d)[64], uint64_t da, uint64_t db, int scale_d) {
  asm volatile("{\n.reg .pred p;\n"
    "setp.ne.b32 p, %66, 0;\n"
    "wgmma.mma_async.sync.aligned.m64n128k16.f32.bf16.bf16 "
    "{%0, %1, %2, %3, %4, %5, %6, %7, %8, %9, %10, %11, %12, %13, %14, %15, %16, %17, %18, %19, %20, %21, %22, %23, %24, %25, %26, %27, %28, %29, %30, %31, %32, %33, %34, %35, %36, %37, %38, %39, %40, %41, %42, %43, %44, %45, %46, %47, %48, %49, %50, %51, %52, %53, %54, %55, %56, %57, %58, %59, %60, %61, %62, %63}, "
    "%64, %65, p, 1, 1, %67, %68;\n}\n"
    : "+f"(d[0]), "+f"(d[1]), "+f"(d[2]), "+f"(d[3]), "+f"(d[4]), "+f"(d[5]), "+f"(d[6]), "+f"(d[7]), "+f"(d[8]), "+f"(d[9]), "+f"(d[10]), "+f"(d[11]), "+f"(d[12]), "+f"(d[13]), "+f"(d[14]), "+f"(d[15]), "+f"(d[16]), "+f"(d[17]), "+f"(d[18]), "+f"(d[19]), "+f"(d[20]), "+f"(d[21]), "+f"(d[22]), "+f"(d[23]), "+f"(d[24]), "+f"(d[25]), "+f"(d[26]), "+f"(d[27]), "+f"(d[28]), "+f"(d[29]), "+f"(d[30]), "+f"(d[31]), "+f"(d[32]), "+f"(d[33]), "+f"(d[34]), "+f"(d[35]), "+f"(d[36]), "+f"(d[37]), "+f"(d[38]), "+f"(d[39]), "+f"(d[40]), "+f"(d[41]), "+f"(d[42]), "+f"(d[43]), "+f"(d[44]), "+f"(d[45]), "+f"(d[46]), "+f"(d[47]), "+f"(d[48]), "+f"(d[49]), "+f"(d[50]), "+f"(d[51]), "+f"(d[52]), "+f"(d[53]), "+f"(d[54]), "+f"(d[55]), "+f"(d[56]), "+f"(d[57]), "+f"(d[58]), "+f"(d[59]), "+f"(d[60]), "+f"(d[61]), "+f"(d[62]), "+f"(d[63])
    : "l"(da), "l"(db), "r"(scale_d), "n"(TA), "n"(TB));
}
template<int TA, int TB> __device__ __forceinline__ void wgmma_ss_n160(float (&d)[80], uint64_t da, uint64_t db, int scale_d) {
  asm volatile("{\n.reg .pred p;\n"
    "setp.ne.b32 p, %82, 0;\n"
    "wgmma.mma_async.sync.aligned.m64n160k16.f32.bf16.bf16 "
    "{%0, %1, %2, %3, %4, %5, %6, %7, %8, %9, %10, %11, %12, %13, %14, %15, %16, %17, %18, %19, %20, %21, %22, %23, %24, %25, %26, %27, %28, %29, %30, %31, %32, %33, %34, %35, %36, %37, %38, %39, %40, %41, %42, %43, %44, %45, %46, %47, %48, %49, %50, %51, %52, %53, %54, %55, %56, %57, %58, %59, %60, %61, %62, %63, %64, %65, %66, %67, %68, %69, %70, %71, %72, %73, %74, %75, %76, %77, %78, %79}, "
    "%80, %81, p, 1, 1, %83, %84;\n}\n"
    : "+f"(d[0]), "+f"(d[1]), "+f"(d[2]), "+f"(d[3]), "+f"(d[4]), "+f"(d[5]), "+f"(d[6]), "+f"(d[7]), "+f"(d[8]), "+f"(d[9]), "+f"(d[10]), "+f"(d[11]), "+f"(d[12]), "+f"(d[13]), "+f"(d[14]), "+f"(d[15]), "+f"(d[16]), "+f"(d[17]), "+f"(d[18]), "+f"(d[19]), "+f"(d[20]), "+f"(d[21]), "+f"(d[22]), "+f"(d[23]), "+f"(d[24]), "+f"(d[25]), "+f"(d[26]), "+f"(d[27]), "+f"(d[28]), "+f"(d[29]), "+f"(d[30]), "+f"(d[31]), "+f"(d[32]), "+f"(d[33]), "+f"(d[34]), "+f"(d[35]), "+f"(d[36]), "+f"(d[37]), "+f"(d[38]), "+f"(d[39]), "+f"(d[40]), "+f"(d[41]), "+f"(d[42]), "+f"(d[43]), "+f"(d[44]), "+f"(d[45]), "+f"(d[46]), "+f"(d[47]), "+f"(d[48]), "+f"(d[49]), "+f"(d[50]), "+f"(d[51]), "+f"(d[52]), "+f"(d[53]), "+f"(d[54]), "+f"(d[55]), "+f"(d[56]), "+f"(d[57]), "+f"(d[58]), "+f"(d[59]), "+f"(d[60]), "+f"(d[61]), "+f"(d[62]), "+f"(d[63]), "+f"(d[64]), "+f"(d[65]), "+f"(d[66]), "+f"(d[67]), "+f"(d[68]), "+f"(d[69]), "+f"(d[70]), "+f"(d[71]), "+f"(d[72]), "+f"(d[73]), "+f"(d[74]), "+f"(d[75]), "+f"(d[76]), "+f"(d[77]), "+f"(d[78]), "+f"(d[79])
    : "l"(da), "l"(db), "r"(scale_d), "n"(TA), "n"(TB));
}
template<int TB> __device__ __forceinline__ void wgmma_rs_n64_init(float (&d)[32], const uint32_t (&a)[4], uint64_t db) {
  asm volatile("{\n.reg .pred p;\nsetp.ne.b32 p, 0, 0;\n"
    "wgmma.mma_async.sync.aligned.m64n64k16.f32.bf16.bf16 "
    "{%0, %1, %2, %3, %4, %5, %6, %7, %8, %9, %10, %11, %12, %13, %14, %15, %16, %17, %18, %19, %20, %21, %22, %23, %24, %25, %26, %27, %28, %29, %30, %31}, "
    "{%32, %33, %34, %35}, %36, p, 1, 1, %37;\n}\n"
    : "=f"(d[0]), "=f"(d[1]), "=f"(d[2]), "=f"(d[3]), "=f"(d[4]), "=f"(d[5]), "=f"(d[6]), "=f"(d[7]), "=f"(d[8]), "=f"(d[9]), "=f"(d[10]), "=f"(d[11]), "=f"(d[12]), "=f"(d[13]), "=f"(d[14]), "=f"(d[15]), "=f"(d[16]), "=f"(d[17]), "=f"(d[18]), "=f"(d[19]), "=f"(d[20]), "=f"(d[21]), "=f"(d[22]), "=f"(d[23]), "=f"(d[24]), "=f"(d[25]), "=f"(d[26]), "=f"(d[27]), "=f"(d[28]), "=f"(d[29]), "=f"(d[30]), "=f"(d[31])
    : "r"(a[0]), "r"(a[1]), "r"(a[2]), "r"(a[3]), "l"(db), "n"(TB));
}
template<int TA, int TB> __device__ __forceinline__ void wgmma_ss_n128_init(float (&d)[64], uint64_t da, uint64_t db) {
  asm volatile("{\n.reg .pred p;\nsetp.ne.b32 p, 0, 0;\n"
    "wgmma.mma_async.sync.aligned.m64n128k16.f32.bf16.bf16 "
    "{%0, %1, %2, %3, %4, %5, %6, %7, %8, %9, %10, %11, %12, %13, %14, %15, %16, %17, %18, %19, %20, %21, %22, %23, %24, %25, %26, %27, %28, %29, %30, %31, %32, %33, %34, %35, %36, %37, %38, %39, %40, %41, %42, %43, %44, %45, %46, %47, %48, %49, %50, %51, %52, %53, %54, %55, %56, %57, %58, %59, %60, %61, %62, %63}, "
    "%64, %65, p, 1, 1, %66, %67;\n}\n"
    : "=f"(d[0]), "=f"(d[1]), "=f"(d[2]), "=f"(d[3]), "=f"(d[4]), "=f"(d[5]), "=f"(d[6]), "=f"(d[7]), "=f"(d[8]), "=f"(d[9]), "=f"(d[10]), "=f"(d[11]), "=f"(d[12]), "=f"(d[13]), "=f"(d[14]), "=f"(d[15]), "=f"(d[16]), "=f"(d[17]), "=f"(d[18]), "=f"(d[19]), "=f"(d[20]), "=f"(d[21]), "=f"(d[22]), "=f"(d[23]), "=f"(d[24]), "=f"(d[25]), "=f"(d[26]), "=f"(d[27]), "=f"(d[28]), "=f"(d[29]), "=f"(d[30]), "=f"(d[31]), "=f"(d[32]), "=f"(d[33]), "=f"(d[34]), "=f"(d[35]), "=f"(d[36]), "=f"(d[37]), "=f"(d[38]), "=f"(d[39]), "=f"(d[40]), "=f"(d[41]), "=f"(d[42]), "=f"(d[43]), "=f"(d[44]), "=f"(d[45]), "=f"(d[46]), "=f"(d[47]), "=f"(d[48]), "=f"(d[49]), "=f"(d[50]), "=f"(d[51]), "=f"(d[52]), "=f"(d[53]), "=f"(d[54]), "=f"(d[55]), "=f"(d[56]), "=f"(d[57]), "=f"(d[58]), "=f"(d[59]), "=f"(d[60]), "=f"(d[61]), "=f"(d[62]), "=f"(d[63])
    : "l"(da), "l"(db), "n"(TA), "n"(TB));
}
template<int TA, int TB> __device__ __forceinline__ void wgmma_ss_n160_init(float (&d)[80], uint64_t da, uint64_t db) {
  asm volatile("{\n.reg .pred p;\nsetp.ne.b32 p, 0, 0;\n"
    "wgmma.mma_async.sync.aligned.m64n160k16.f32.bf16.bf16 "
    "{%0, %1, %2, %3, %4, %5, %6, %7, %8, %9, %10, %11, %12, %13, %14, %15, %16, %17, %18, %19, %20, %21, %22, %23, %24, %25, %26, %27, %28, %29, %30, %31, %32, %33, %34, %35, %36, %37, %38, %39, %40, %41, %42, %43, %44, %45, %46, %47, %48, %49, %50, %51, %52, %53, %54, %55, %56, %57, %58, %59, %60, %61, %62, %63, %64, %65, %66, %67, %68, %69, %70, %71, %72, %73, %74, %75, %76, %77, %78, %79}, "
    "%80, %81, p, 1, 1, %82, %83;\n}\n"
    : "=f"(d[0]), "=f"(d[1]), "=f"(d[2]), "=f"(d[3]), "=f"(d[4]), "=f"(d[5]), "=f"(d[6]), "=f"(d[7]), "=f"(d[8]), "=f"(d[9]), "=f"(d[10]), "=f"(d[11]), "=f"(d[12]), "=f"(d[13]), "=f"(d[14]), "=f"(d[15]), "=f"(d[16]), "=f"(d[17]), "=f"(d[18]), "=f"(d[19]), "=f"(d[20]), "=f"(d[21]), "=f"(d[22]), "=f"(d[23]), "=f"(d[24]), "=f"(d[25]), "=f"(d[26]), "=f"(d[27]), "=f"(d[28]), "=f"(d[29]), "=f"(d[30]), "=f"(d[31]), "=f"(d[32]), "=f"(d[33]), "=f"(d[34]), "=f"(d[35]), "=f"(d[36]), "=f"(d[37]), "=f"(d[38]), "=f"(d[39]), "=f"(d[40]), "=f"(d[41]), "=f"(d[42]), "=f"(d[43]), "=f"(d[44]), "=f"(d[45]), "=f"(d[46]), "=f"(d[47]), "=f"(d[48]), "=f"(d[49]), "=f"(d[50]), "=f"(d[51]), "=f"(d[52]), "=f"(d[53]), "=f"(d[54]), "=f"(d[55]), "=f"(d[56]), "=f"(d[57]), "=f"(d[58]), "=f"(d[59]), "=f"(d[60]), "=f"(d[61]), "=f"(d[62]), "=f"(d[63]), "=f"(d[64]), "=f"(d[65]), "=f"(d[66]), "=f"(d[67]), "=f"(d[68]), "=f"(d[69]), "=f"(d[70]), "=f"(d[71]), "=f"(d[72]), "=f"(d[73]), "=f"(d[74]), "=f"(d[75]), "=f"(d[76]), "=f"(d[77]), "=f"(d[78]), "=f"(d[79])
    : "l"(da), "l"(db), "n"(TA), "n"(TB));
}

__device__ __forceinline__ void ln_row(uint32_t (&v)[20]) {
  float s = 0.f;
#pragma unroll
  for (int i = 0; i < 20; i++) s += bf_lo(v[i]) + bf_hi(v[i]);
#pragma unroll
  for (int o = 8; o > 0; o >>= 1) s += __shfl_xor_sync(0xffffffffu, s, o);
  const float mean = s * (1.f / DM);
  float q = 0.f;
#pragma unroll
  for (int i = 0; i < 20; i++) { const float d0 = bf_lo(v[i]) - mean, d1 = bf_hi(v[i]) - mean; q = fmaf(d0, d0, q); q = fmaf(d1, d1, q); }
#pragma unroll
  for (int o = 8; o > 0; o >>= 1) q += __shfl_xor_sync(0xffffffffu, q, o);
  const uint32_t mb = pack_bf16(mean, mean);
  const float inv = rcp_fast(rbf16(sqrt_fast(rbf16(rbf16(q * (1.f / DM)) + 1e-5f))));
#pragma unroll
  for (int i = 0; i < 20; i++) { const uint32_t d = bf2_sub(v[i], mb); v[i] = pack_bf16(bf_lo(d) * inv, bf_hi(d) * inv); }
}

constexpr int NST = 6;
constexpr int STAGE = 36864;
constexpr int SMEM_BYTES = NST * STAGE + 8192 + 256 + 1024;
__device__ __forceinline__ uint32_t tail_slab(uint32_t base, int w8) { return base + (w8 < NST ? w8 * STAGE + 32768 : NST * STAGE + (w8 - NST) * 4096); }
struct Ring {
  uint32_t stage, phase;
  __device__ __forceinline__ void advance() { if (++stage == NST) { stage = 0; phase ^= 1; } }
  __device__ __forceinline__ void skip(int n) { stage = (stage + n) % NST; }
};
constexpr float SCALE_LOG2E = 0.08838834764831845f * 1.4426950408889634f;
constexpr float LAZY_SUM = 4096.f;
constexpr int EARLY = 6;
constexpr int ACT_NR = 4;
constexpr int XM = 2;
constexpr int STG_DELAY = 3;
constexpr int ST_DELAY = 5000;
constexpr int TAIL_J = 10, PF_NEXT = 16;
constexpr int DA = 30, DB = 16, DZ = 22, DY = 10, DX = 33;
#define PP_SYNC() bar_sync(2 + wg, 256)
#define PP_ARRIVE() bar_arrive(2 + (wg ^ 1), 256)

enum { T_END = 0, T_ATT = 1, T_MLP1 = 2, T_PART = 3, T_OWN = 4 };
constexpr int NCL = 66, MAXI = 8;
constexpr int ZEND = 58 - (28 - 8 * XM);
struct Params {
  CUtensorMap xn, wq, k, v, o, wo, w1, h, w2, ut, ut_st, out_st, x_ld, o_st;
  const bf16 *x, *b1, *b2;
  uint32_t sched[NCL][MAXI];
  uint8_t perm[NCL];
};

__device__ __forceinline__ int final_row(int cluster_id, uint32_t ticket_bar, uint32_t ticket_val) {
  if (cluster_id >= ZEND) return cluster_id;
  mbar_wait(ticket_bar, 0);
  uint32_t v; asm volatile("ld.shared.u32 %0, [%1];" : "=r"(v) : "r"(ticket_val) : "memory");
  return __shfl_sync(0xffffffffu, v, 0);
}
__device__ __forceinline__ void release_stage(uint32_t empty_bar, int lane) {
  if (lane < 2) mbar_arrive_cluster(empty_bar, lane);
}
__device__ __forceinline__ void row_max(const float (&s)[32], float& mx0, float& mx1) {
  mx0 = fmaxf(s[0], s[1]); mx1 = fmaxf(s[2], s[3]);
  float mx0b = fmaxf(s[4], s[5]), mx1b = fmaxf(s[6], s[7]);
#pragma unroll
  for (int j = 2; j < 8; j += 2) {
    mx0 = fmaxf(mx0, fmaxf(s[4*j], s[4*j+1])); mx1 = fmaxf(mx1, fmaxf(s[4*j+2], s[4*j+3]));
    mx0b = fmaxf(mx0b, fmaxf(s[4*j+4], s[4*j+5])); mx1b = fmaxf(mx1b, fmaxf(s[4*j+6], s[4*j+7]));
  }
  mx0 = fmaxf(mx0, mx0b); mx1 = fmaxf(mx1, mx1b);
  mx0 = fmaxf(mx0, __shfl_xor_sync(0xffffffffu, mx0, 1)); mx1 = fmaxf(mx1, __shfl_xor_sync(0xffffffffu, mx1, 1));
  mx0 = fmaxf(mx0, __shfl_xor_sync(0xffffffffu, mx0, 2)); mx1 = fmaxf(mx1, __shfl_xor_sync(0xffffffffu, mx1, 2));
}
__device__ __forceinline__ void scale_tile(float (&s)[32], float nm0, float nm1) {
#pragma unroll
  for (int i = 0; i < 32; i++) asm volatile("fma.rn.f32 %0, %0, %1, %2;" : "+f"(s[i]) : "f"(SCALE_LOG2E), "f"((i & 2) ? nm1 : nm0));
}
__device__ __forceinline__ void exp_tile(const float (&x)[32], uint32_t (&p)[4][4], float& a0, float& a1) {
#pragma unroll
  for (int k = 0; k < 4; k++) {
#pragma unroll
    for (int h = 0; h < 2; h++) {
      const float e0 = ex2(x[8*k+4*h]), e1 = ex2(x[8*k+4*h+1]), e2 = ex2(x[8*k+4*h+2]), e3 = ex2(x[8*k+4*h+3]);
      if (k == 0 && h == 0) { a0 = e0; a1 = e2; } else { a0 += e0; a1 += e2; }
      a0 += e1; a1 += e3;
      p[k][2*h] = pack_bf16(e0, e1); p[k][2*h+1] = pack_bf16(e2, e3);
    }
  }
}
__device__ __forceinline__ void fence_p(uint32_t (&p)[4][4]) {
#pragma unroll
  for (int k = 0; k < 4; k++)
#pragma unroll
    for (int i = 0; i < 4; i++) asm volatile("" : "+r"(p[k][i]) :: "memory");
}
__device__ __forceinline__ void issue_qk(float (&s)[32], const uint32_t (&q)[8][4], uint32_t sk) {
  const uint64_t d0 = make_desc(sk, 16, 1024);
#pragma unroll
  for (int k = 0; k < 8; k++) {
    if (k == 0) wgmma_rs_n64_init<0>(s, q[k], d0);
    else wgmma_rs_n64<0>(s, q[k], d0 + (((k >> 2) * 8192 + (k & 3) * 32) >> 4), 1);
  }
}
__device__ __forceinline__ void issue_pv(float (&o)[64], const uint32_t (&p)[4][4], uint32_t sv) {
  const uint64_t d0 = make_desc(sv, 8192, 1024);
#pragma unroll
  for (int k = 0; k < 4; k++) wgmma_rs_n128<1>(o, p[k], d0 + ((k * 2048) >> 4), 1);
}
__device__ __forceinline__ void softmax_step(float (&x)[32], float (&s_other)[32], uint32_t (&p)[4][4], uint32_t (&p_other)[4][4], float (&o)[64],
                                             float& nm0, float& nm1, float (&l)[2], uint32_t scratch) {
  float a0, a1;
  exp_tile(x, p, a0, a1);
  const bool big = !(a0 + a1 <= LAZY_SUM);
  if (big) asm volatile("st.shared.f32 [%0], %1;" :: "r"(scratch), "f"(a0) : "memory");
  const bool trip = __any_sync(0xffffffffu, big);
  wgmma_wait<0>(); fence_regs(o); fence_regs(s_other); fence_p(p_other);
  if (__builtin_expect(trip, 0)) {
    float d0, d1; row_max(x, d0, d1);
    d0 = fmaxf(d0, 0.f); d1 = fmaxf(d1, 0.f);
    const float sc0 = ex2(-d0), sc1 = ex2(-d1);
    nm0 -= d0; nm1 -= d1; l[0] *= sc0; l[1] *= sc1;
#pragma unroll
    for (int i = 0; i < 32; i++) x[i] -= (i & 2) ? d1 : d0;
    exp_tile(x, p, a0, a1);
#pragma unroll
    for (int i = 0; i < 16; i++) { o[4*i] *= sc0; o[4*i+1] *= sc0; o[4*i+2] *= sc1; o[4*i+3] *= sc1; }
  }
  l[0] += a0; l[1] += a1;
}
template<bool FIRST> __device__ __forceinline__ void issue_qproj(float (&qa)[64], uint32_t sp, int wg) {
  const uint64_t da = make_desc(sp + wg * 8192, 16, 1024), db = make_desc(sp + 16384, 8192, 1024);
  wgmma_fence();
#pragma unroll
  for (int k = 0; k < 4; k++) {
    if (FIRST && k == 0) wgmma_ss_n128_init<0, 1>(qa, da, db);
    else wgmma_ss_n128<0, 1>(qa, da + ((k * 32) >> 4), db + ((k * 2048) >> 4), 1);
  }
  wgmma_commit();
}

template<int K0, int N = 4> __device__ __forceinline__ void stage_o(const float (&o)[64], float i0, float i1, uint32_t ob, int mrow, int lane) {
#pragma unroll
  for (int k = K0; k < K0 + N; k++) {
    const uint32_t r0 = pack_bf16(o[8*k] * i0, o[8*k+1] * i0), r1 = pack_bf16(o[8*k+2] * i1, o[8*k+3] * i1);
    const uint32_t r2 = pack_bf16(o[8*k+4] * i0, o[8*k+5] * i0), r3 = pack_bf16(o[8*k+6] * i1, o[8*k+7] * i1);
    const int chunk = (k & 3) * 2 + (lane >> 4);
    stmatrix_x4(ob + (k >> 2) * 2048 + ((chunk ^ (mrow & 7)) << 4), r0, r1, r2, r3);
  }
}
__device__ __forceinline__ void finish_qproj(float (&qa)[64], uint32_t (&q)[8][4], int cfirst, uint32_t prev, Ring& r, uint32_t base, uint32_t full, uint32_t empty, int wg, int lane) {
#pragma unroll 1
  for (int c = cfirst; c < 10; c++) {
    mbar_wait(full + 8 * r.stage, r.phase);
    if (wg == 1 && c == 8) bar_sync(9, 256);
    issue_qproj<false>(qa, base + r.stage * STAGE, wg);
    if (wg == 0 && c == 9) bar_arrive(9, 256);
    if (c > 0) { wgmma_wait<1>(); release_stage(prev, lane); }
    prev = empty + 8 * r.stage;
    r.advance();
  }
  wgmma_wait<0>(); fence_regs(qa);
  release_stage(prev, lane);
#pragma unroll
  for (int k = 0; k < 32; k++) q[k >> 2][k & 3] = pack_bf16(qa[2*k], qa[2*k+1]);
}

__device__ __forceinline__ float tanh_fast(float x) { float y; asm("tanh.approx.f32 %0, %1;" : "=f"(y) : "f"(x)); return y; }
template<int NR, bool GELU>
__device__ __forceinline__ void act_step(uint32_t (&t)[40]) {
  uint32_t u[NR];
#pragma unroll
  for (int j = 0; j < NR; j++) {
    const float x0 = bf_lo(t[j]), x1 = bf_hi(t[j]);
    const float h0 = 0.5f * x0, h1 = 0.5f * x1;
    constexpr float k1 = 0.7978845608028654f, k3 = 0.7978845608028654f * 0.044715f;
    const float z0 = GELU ? x0 * fmaf(x0 * x0, k3, k1) : h0, z1 = GELU ? x1 * fmaf(x1 * x1, k3, k1) : h1;
    u[j] = pack_bf16(fmaf(h0, tanh_fast(z0), h0), fmaf(h1, tanh_fast(z1), h1));
  }
#pragma unroll
  for (int j = 0; j < 40 - NR; j++) t[j] = t[j + NR];
#pragma unroll
  for (int j = 0; j < NR; j++) t[40 - NR + j] = u[j];
}
template<int TA, bool FIRST>
__device__ __forceinline__ void issue_chunk(float (&acc)[80], uint32_t sp, int wg) {
  const uint64_t da = make_desc(sp + wg * 8192, 16, 1024), db = make_desc64(sp + 16384, 2048, 512);
  wgmma_fence();
#pragma unroll
  for (int k = 0; k < 4; k++) {
    if (FIRST && k == 0) wgmma_ss_n160_init<TA, 1>(acc, da, db);
    else wgmma_ss_n160<TA, 1>(acc, da + (((TA ? 2048 : 32) * k) >> 4), db + (((k >> 1) * 10240 + (k & 1) * 1024) >> 4), 1);
  }
  wgmma_commit();
}
template<int TA, bool ACT, int LAG = 0>
__device__ __forceinline__ uint32_t gemm_loop(float (&acc)[80], uint32_t (&t)[40], uint32_t prev, Ring& r, int n, uint32_t base, uint32_t full, uint32_t empty, int wg, int lane) {
#pragma unroll 1
  for (int c = 0; c < n; c++) {
    mbar_wait(full + 8 * r.stage, r.phase);
    if (LAG && wg == 1 && c == n - LAG) bar_sync(9, 256);
    issue_chunk<TA, false>(acc, base + r.stage * STAGE, wg);
    if (LAG && wg == 0 && c == n - 1) bar_arrive(9, 256);
    if (ACT) { act_step<ACT_NR, false>(t); order_after(t[39], full + 128); }
    wgmma_wait<1>();
    if (prev) release_stage(prev, lane);
    prev = empty + 8 * r.stage;
    r.advance();
  }
  return prev;
}
__device__ __forceinline__ uint32_t tile_addr(uint32_t sp, int warp, int lane) {
  const int mrow = warp * 16 + (lane & 7) + ((lane >> 3) & 1) * 8;
  return sp + mrow * 64 + (((lane >> 4) ^ ((mrow >> 1) & 3)) << 4);
}
__device__ __forceinline__ void stage_tile(const uint32_t (&t)[40], Ring& r, uint32_t base, uint32_t full, uint32_t staged, int wg, int warp, int lane) {
  if (wg == 1) r.advance();
  mbar_wait(full + 8 * r.stage, r.phase);
  const uint32_t ob = tile_addr(base + r.stage * STAGE, warp, lane);
#pragma unroll
  for (int k = 0; k < 10; k++) {
    const uint32_t addr = (ob ^ ((k & 1) << 5)) + (k >> 1) * 4096;
    stmatrix_x4(addr, t[4*k], t[4*k+1], t[4*k+2], t[4*k+3]);
  }
  fence_async_smem();
  __syncwarp();
  if (lane == 0) mbar_arrive(staged);
  r.advance();
  if (wg == 0) r.advance();
}
__global__ void __cluster_dims__(2, 1, 1) __launch_bounds__(384, 1) fused_kernel(const __grid_constant__ Params P) {
  extern __shared__ char smem_raw[];
  uint32_t lnv[20];
  if (blockIdx.x < 128 && threadIdx.x < 256) {
    const uint4* src = (const uint4*)(P.x + (blockIdx.x * 16 + (threadIdx.x >> 4)) * DM) + (threadIdx.x & 15);
#pragma unroll
    for (int i = 0; i < 5; i++) { const uint4 t = __ldg(src + 16 * i); lnv[4*i] = t.x; lnv[4*i+1] = t.y; lnv[4*i+2] = t.z; lnv[4*i+3] = t.w; }
  }
  const uint32_t base = (smem_u32(smem_raw) + 1023) & ~1023u;
  const uint32_t full = base + NST * STAGE + 8192, empty = full + 8 * NST, staged = empty + 8 * NST, tail_free = staged + 8, ticket_bar = tail_free + 8, ticket_val = full + 136;
  const int wg = __shfl_sync(0xffffffffu, threadIdx.x / 128, 0);
  const int lane = threadIdx.x & 31;
  const uint32_t rank = cluster_ctarank();
  const int cluster_id = P.perm[blockIdx.x >> 1];
  if (threadIdx.x == 256) {
    for (int i = 0; i < NST; i++) { mbar_init(full + 8 * i, 1); mbar_init(empty + 8 * i, 16); }
    mbar_init(staged, 8); mbar_init(tail_free, 1); mbar_init(ticket_bar, 1);
    mbar_expect_tx(ticket_bar, 4);
    asm volatile("fence.mbarrier_init.release.cluster;" ::: "memory");
  }
  __syncwarp();
  cluster_arrive_relaxed();
  if (threadIdx.x >> 5 == 8) {
    const uint32_t w = P.sched[cluster_id][0];
    const bool att = (w & 7) == T_ATT;
    const int a = (w >> 3) & 31;
    const CUtensorMap* m = att ? &P.wq : &P.w1;
    const int col = att ? a * 128 : a * 256 + rank * 128;
#pragma unroll 1
    for (int c = 0; c < EARLY; c++) {
      if (elect_one()) {
        const uint32_t dst = base + c * STAGE + (att ? 16384 : 0);
        mbar_expect_tx(full + 8 * c, att ? 32768 : STAGE);
        tma_load_2d(dst, m, col, c * 64, full + 8 * c);
        tma_load_2d(dst + 8192, m, col + 64, c * 64, full + 8 * c);
      }
    }
    if (att) {
      const int k = ((w >> 8) & 7);
      if (elect_one()) {
        const CUtensorMap* mp = k < 4 ? &P.wq : k < 7 ? &P.k : &P.v;
        const int c0 = k < 4 ? col + rank * 64 : rank * 64, c1 = k < 4 ? (6 + k) * 64 : a * 2048 + (k < 7 ? k - 4 : 0) * 64;
        tma_prefetch_2d(mp, c0, c1);
      }
    }
  }
  if (wg == 2) {
    asm volatile("setmaxnreg.dec.sync.aligned.u32 24;");
    const int pw = __shfl_sync(0xffffffffu, (threadIdx.x >> 5) & 3, 0);
    if (pw == 0) {
      if (lane < 14) prefetch_map(&P.xn + lane);
      cluster_wait();
      Ring r{0, 1};
      uint32_t ln_mask = 0;
      int stg_in = -1, row = cluster_id;
#pragma unroll 1
      for (int it = 0; it < MAXI; it++) {
        const uint32_t w = __shfl_sync(0xffffffffu, P.sched[row][it], 0);
        const int type = w & 7, a = (w >> 3) & 31, b = (w >> 8) & 7, c0 = (w >> 11) & 127, c1 = (w >> 18) & 127, e = (w >> 25) & 3;
        if (type == T_END) break;
        int nstaging = 2;
        const int m0 = a * 256 + rank * 128;
        if (type == T_ATT) {
          const int row0 = b * 256 + rank * 128;
          const uint32_t wn = P.sched[cluster_id][it + 1];
          const int an = (wn & 7) == T_ATT ? (int)(wn >> 3) & 31 : -1;
          const int npre = it == 0 ? EARLY : 0;
          wait_flags(ln_mask, b * 2 + rank, &g_cnt[C_XN], 16, 8, lane);
#pragma unroll 1
          for (int c = 0; c < 10; c++) {
            mbar_wait(empty + 8 * r.stage, r.phase);
            const uint32_t fb = full + 8 * r.stage, sp = base + r.stage * STAGE;
            if (elect_one()) {
              if (c >= npre) {
                mbar_expect_tx(fb, 32768);
                tma_load_2d_mc(sp + 16384 + rank * 8192, &P.wq, a * 128 + rank * 64, c * 64, fb, 3);
              }
              tma_load_2d(sp, &P.xn, c * 64, row0, fb);
            }
            r.advance();
          }
#pragma unroll 1
          for (int j = 0; j < 32; j++) {
            mbar_wait(empty + 8 * r.stage, r.phase);
            const uint32_t fb = full + 8 * r.stage, sp = base + r.stage * STAGE;
            const CUtensorMap* m0p = j < 31 ? &P.k : &P.v;
            const CUtensorMap* m1p = j > 0 ? &P.v : &P.k;
            const int k0 = j == 0 ? 0 : j < 31 ? j + 1 : 30, k1 = j == 0 ? 1 : j < 31 ? j - 1 : 31;
            if (elect_one()) {
              mbar_expect_tx(fb, 32768);
              tma_load_2d_mc(sp + rank * 8192, m0p, rank * 64, a * 2048 + k0 * 64, fb, 3);
              tma_load_2d_mc(sp + 16384 + rank * 8192, m1p, rank * 64, a * 2048 + k1 * 64, fb, 3);
              if (j == PF_NEXT && an >= 0) {
                const int k = (wn >> 8) & 7;
                tma_prefetch_2d(&P.wq, an * 128 + rank * 64, k * 64);
                if (k < 2) tma_prefetch_2d(&P.wq, an * 128 + rank * 64, (8 + k) * 64);
                else tma_prefetch_2d(k < 6 ? &P.k : &P.v, rank * 64, an * 2048 + ((k - 2) & 3) * 64);
              }
            }
            r.advance();
          }
          nstaging = (wn & 7) == T_END;
          stg_in = an < 0 ? STG_DELAY : -1;
          if (an < 0) row = final_row(cluster_id, ticket_bar, ticket_val);
        } else {
          uint32_t mask = 0;
          if (type == T_MLP1 || type == T_OWN) {
            const CUtensorMap* ma = type == T_MLP1 ? &P.w1 : &P.w2;
            const CUtensorMap* mb = type == T_MLP1 ? &P.h : &P.ut;
            const int n = type == T_MLP1 ? 32 : 27;
            const int npre = it == 0 ? EARLY : 0;
            const bool m1 = type == T_MLP1;
#pragma unroll 1
            for (int c = 0; c < n; c++) {
              if (stg_in-- == 0) {
                mbar_wait(empty + 8 * r.stage, r.phase);
                if (elect_one()) mbar_arrive(full + 8 * r.stage);
                r.advance();
              }
              wait_flags(mask, c >> (m1 ? 1 : 2), &g_cnt[m1 ? C_H : C_U + b * 8], m1 ? 16 : 7, m1 ? 8 : 2, lane);
              mbar_wait(empty + 8 * r.stage, r.phase);
              const uint32_t fb = full + 8 * r.stage, sp = base + r.stage * STAGE;
              if (elect_one()) {
                if (c >= npre) {
                  mbar_expect_tx(fb, STAGE);
                  tma_load_2d(sp, ma, m0, c * 64, fb);
                  tma_load_2d(sp + 8192, ma, m0 + 64, c * 64, fb);
                }
                tma_load_3d_mc(sp + 16384 + rank * 10240, mb, 0, c * 64 + rank * 32, b * 5, fb, 3);
              }
              r.advance();
            }
          }
          if (type == T_PART || type == T_OWN) {
            mask = 0;
#pragma unroll 1
            for (int c = c0; c < c1; c++) {
              if (stg_in-- == 0) {
                mbar_wait(empty + 8 * r.stage, r.phase);
                if (elect_one()) mbar_arrive(full + 8 * r.stage);
                r.advance();
              }
              wait_flags(mask, c >> 1, &g_cnt[C_O + (a * 2 + rank) * 32], 32, 1, lane);
              mbar_wait(empty + 8 * r.stage, r.phase);
              const uint32_t fb = full + 8 * r.stage, sp = base + r.stage * STAGE;
              if (elect_one()) {
                mbar_expect_tx(fb, STAGE);
                tma_load_2d(sp, &P.o, c * 64, m0, fb);
                tma_load_3d_mc(sp + 16384 + rank * 10240, &P.wo, 0, c * 64 + rank * 32, b * 5, fb, 3);
              }
              r.advance();
            }
          }
          if (type == T_OWN) {
#pragma unroll 1
            for (int q = 0; q < 2; q++) {
              mbar_wait(empty + 8 * r.stage, r.phase);
              if (elect_one()) {
                mbar_expect_tx(full + 8 * r.stage, 20480);
                tma_load_3d(base + r.stage * STAGE, &P.x_ld, 0, m0 + q * 64, b * 5, full + 8 * r.stage);
              }
              r.advance();
            }
            nstaging = 0;
            mask = 0;
            const int slot0 = ((a * 4 + b) * 2 + rank) * 3;
#pragma unroll 1
            for (int q = 0; q < 2 * e; q++) {
              wait_flags(mask, q >> 1, &g_cnt[C_PART + slot0], 3, 1, lane);
              mbar_wait(empty + 8 * r.stage, r.phase);
              if (elect_one()) {
                mbar_expect_tx(full + 8 * r.stage, 20480);
                bulk_load(base + r.stage * STAGE, g_part + (slot0 * 2 + q) * 1280, 20480, full + 8 * r.stage);
              }
              r.advance();
            }
          }
        }
#pragma unroll 1
        for (int q = 0; q < nstaging; q++) {
          mbar_wait(empty + 8 * r.stage, r.phase);
          if (elect_one()) mbar_arrive(full + 8 * r.stage);
          r.advance();
        }
      }
      uint32_t t = 0;
      if (lane == 0) asm volatile("atom.acq_rel.gpu.global.add.u32 %0, [%1], 1;" : "=r"(t) : "l"(&g_cnt[C_DONE]) : "memory");
      t = __shfl_sync(0xffffffffu, t, 0);
      if (t == gridDim.x - 1) {
        __syncwarp();
        for (int i = lane; i < C_TOTAL / 4; i += 32) ((uint4*)g_cnt)[i] = make_uint4(0, 0, 0, 0);
      }
    } else {
      cluster_wait();
      if (pw == 1) {
        Ring r{0, 0};
        uint32_t sph = 0;
        const bool leader = elect_one();
        int row = cluster_id;
        if (blockIdx.x < 128) {
          bar_sync(7, 288);
          if (leader) red_release(&g_cnt[C_H + (blockIdx.x >> 3)], 1);
          __syncwarp();
        }
#pragma unroll 1
        for (int it = 0; it < MAXI; it++) {
          const uint32_t w = __shfl_sync(0xffffffffu, P.sched[row][it], 0);
          const int type = w & 7, a = (w >> 3) & 31, b = (w >> 8) & 7, c0 = (w >> 11) & 127, c1 = (w >> 18) & 127, e = (w >> 25) & 3;
          if (type == T_END || type == T_OWN) break;
          r.skip(type == T_ATT ? 42 : type == T_MLP1 ? 32 : c1 - c0);
          const int tnext = P.sched[row][it + 1] & 7;
          const bool tails = type == T_ATT && tnext == T_ATT;
          if (type == T_ATT && !tails) row = final_row(cluster_id, ticket_bar, ticket_val);
          const int nstaging = tails ? 0 : type == T_ATT ? 1 : 2;
          const uint32_t s0 = (r.stage + (type == T_ATT && tnext != T_END ? STG_DELAY : 0)) % NST, s1 = (s0 + 1) % NST;
          r.skip(nstaging);
          const int slot = ((a * 4 + b) * 2 + rank) * 3 + e;
          uint32_t* flag = &g_cnt[type == T_ATT ? C_O + (b * 2 + rank) * 32 + a : type == T_PART ? C_PART + slot : C_U + b * 8 + a];
          mbar_wait(staged, sph); sph ^= 1;
          if (it == 2 && cluster_id < ZEND && rank == 0) {
            uint32_t tk = 0;
            if (leader) tk = atomicAdd(&g_cnt[C_TICKET], 1);
            tk = __reduce_max_sync(0xffffffffu, tk);
            if (lane < 2)
              asm volatile("{\n.reg .b32 a, m;\nmapa.shared::cluster.u32 a, %0, %2;\nmapa.shared::cluster.u32 m, %1, %2;\n"
                           "st.async.weak.shared::cluster.mbarrier::complete_tx::bytes.u32 [a], %3, [m];\n}"
                           :: "r"(ticket_val), "r"(ticket_bar), "r"(lane), "r"(tk) : "memory");
            __syncwarp();
          }
          if (type == T_ATT) {
            const int row0 = b * 256 + rank * 128;
            if (tails) __nanosleep(ST_DELAY);
#pragma unroll
            for (int w8 = 0; w8 < 8; w8++) {
              const uint32_t slab = tails ? tail_slab(base, w8) : base + s0 * STAGE + w8 * 4096;
              if (leader) tma_store_3d(&P.o_st, slab, 0, row0 + w8 * 16, a * 2);
            }
          } else if (type == T_PART) {
            if (leader) {
              bulk_store(g_part + slot * 2 * 1280, base + s0 * STAGE, 20480);
              bulk_store(g_part + (slot * 2 + 1) * 1280, base + s1 * STAGE, 20480);
            }
          } else {
            const int m0 = a * 256 + rank * 128;
            if (leader) {
              tma_store_3d(&P.ut_st, base + s0 * STAGE, 0, m0, b * 5);
              tma_store_3d(&P.ut_st, base + s1 * STAGE, 0, m0 + 64, b * 5);
            }
          }
          if (leader) {
            bulk_commit();
            bulk_wait_read<0>();
            if (tails) mbar_arrive(tail_free);
            if (nstaging > 0) { mbar_arrive_cluster_n(empty + 8 * s0, 0, 8); mbar_arrive_cluster_n(empty + 8 * s0, 1, 8); }
            if (nstaging > 1) { mbar_arrive_cluster_n(empty + 8 * s1, 0, 8); mbar_arrive_cluster_n(empty + 8 * s1, 1, 8); }
            bulk_wait<0>();
            fence_async_global();
            red_release(flag, 1);
          }
          __syncwarp();
        }
      }
    }
    __syncwarp();
    cluster_arrive_relaxed(); cluster_wait();
  } else {
    asm volatile("setmaxnreg.inc.sync.aligned.u32 240;");
    const int warp = (threadIdx.x >> 5) & 3;
    if (blockIdx.x < 128) {
#pragma unroll 1
      for (int pass = 0; pass < 2; pass++) {
        ln_row(lnv);
        uint4* dst = (uint4*)((pass ? g_h : g_xn) + (blockIdx.x * 16 + (threadIdx.x >> 4)) * DM) + (threadIdx.x & 15);
#pragma unroll
        for (int i = 0; i < 5; i++) dst[16 * i] = make_uint4(lnv[4*i], lnv[4*i+1], lnv[4*i+2], lnv[4*i+3]);
        if (pass == 0) {
          bar_sync(1, 256);
          if (threadIdx.x == 0) red_release(&g_cnt[C_XN + (blockIdx.x >> 3)], 1);
        } else bar_arrive(7, 288);
      }
    }
    cluster_wait();
    Ring r{0, 0};
    if (wg == 1) bar_arrive(2, 256);
    uint32_t tail_phase = 1;
    int row = cluster_id;
#pragma unroll 1
    for (int it = 0; it < MAXI; it++) {
      uint32_t w = __shfl_sync(0xffffffffu, P.sched[row][it], 0);
      if ((w & 7) == T_END) break;
      float acc[80];
      int cdone = 0;
      if ((w & 7) == T_ATT) {
        uint32_t q[8][4];
        {
          float qa[64];
          zero_regs(qa);
          finish_qproj(qa, q, 0, 0, r, base, full, empty, wg, lane);
        }
        float o[64], i0, i1;
        uint32_t pb[4][4], vst, ob;
        const int mrow = (lane & 7) + ((lane >> 3) & 1) * 8;
#pragma unroll 1
        for (;;) {
          w = __shfl_sync(0xffffffffu, P.sched[cluster_id][it + 1], 0);
          const bool nxt = (w & 7) == T_ATT;
          {
            float sa[32], sb[32];
            uint32_t pa[4][4];
            float l[2], nm0, nm1;
            mbar_wait(full + 8 * r.stage, r.phase);
            uint32_t rel = empty + 8 * r.stage;
            wgmma_fence();
            issue_qk(sa, q, base + r.stage * STAGE);
            wgmma_commit();
            issue_qk(sb, q, base + r.stage * STAGE + 16384);
            wgmma_commit();
            r.advance();
            zero_regs(o); fence_regs(o);
#pragma unroll
            for (int i = 0; i < 16; i++) pb[i >> 2][i & 3] = 0;
            wgmma_wait<1>(); fence_regs(sa);
            row_max(sa, nm0, nm1); nm0 *= -SCALE_LOG2E; nm1 *= -SCALE_LOG2E;
            scale_tile(sa, nm0, nm1);
            l[0] = 0.f; l[1] = 0.f;
            vst = r.stage; mbar_wait(full + 8 * r.stage, r.phase); r.advance();
#pragma unroll 1
            for (int j = 0; j < 15; j++) {
              softmax_step(sa, sb, pa, pb, o, nm0, nm1, l, full + 128);
              if (j == TAIL_J) mbar_wait(tail_free, tail_phase);
              release_stage(rel, lane);
              const Ring rb = r; r.advance();
              const bool okb = mbar_try_wait(full + 8 * rb.stage, rb.phase);
              PP_SYNC();
              wgmma_fence();
              issue_qk(sa, q, base + vst * STAGE);
              wgmma_commit();
              if (__builtin_expect(!okb, 0)) mbar_wait(full + 8 * rb.stage, rb.phase);
              scale_tile(sb, nm0, nm1);
              wgmma_fence();
              issue_pv(o, pa, base + vst * STAGE + 16384);
              wgmma_commit();
              PP_ARRIVE();
              if (__builtin_expect(!okb, 0)) mbar_wait(full + 8 * rb.stage, rb.phase);
              softmax_step(sb, sa, pb, pa, o, nm0, nm1, l, full + 128);
              release_stage(empty + 8 * vst, lane);
              const Ring ra = r; r.advance();
              const bool oka = mbar_try_wait(full + 8 * ra.stage, ra.phase);
              PP_SYNC();
              wgmma_fence();
              issue_qk(sb, q, base + rb.stage * STAGE);
              wgmma_commit();
              if (__builtin_expect(!oka, 0)) mbar_wait(full + 8 * ra.stage, ra.phase);
              scale_tile(sa, nm0, nm1);
              wgmma_fence();
              issue_pv(o, pb, base + rb.stage * STAGE + 16384);
              wgmma_commit();
              PP_ARRIVE();
              rel = empty + 8 * rb.stage;
              vst = ra.stage;
            }
            softmax_step(sa, sb, pa, pb, o, nm0, nm1, l, full + 128);
            release_stage(rel, lane);
            wgmma_fence();
            issue_pv(o, pa, base + vst * STAGE);
            wgmma_commit();
            scale_tile(sb, nm0, nm1);
            uint32_t slab = tail_slab(base, wg * 4 + warp);
            mbar_wait(tail_free, tail_phase);
            if (nxt) tail_phase ^= 1;
            else {
              Ring rs = r;
              if ((w & 7) != T_END) { for (int k = 0; k < STG_DELAY; k++) rs.advance(); }
              slab = base + rs.stage * STAGE + (wg * 4 + warp) * 4096;
              mbar_wait(full + 8 * rs.stage, rs.phase);
              row = final_row(cluster_id, ticket_bar, ticket_val);
              w = __shfl_sync(0xffffffffu, P.sched[row][it + 1], 0);
            }
            softmax_step(sb, sa, pb, pa, o, nm0, nm1, l, full + 128);
            wgmma_fence();
            issue_pv(o, pb, base + vst * STAGE + 16384);
            wgmma_commit();
            l[0] += __shfl_xor_sync(0xffffffffu, l[0], 1); l[1] += __shfl_xor_sync(0xffffffffu, l[1], 1);
            l[0] += __shfl_xor_sync(0xffffffffu, l[0], 2); l[1] += __shfl_xor_sync(0xffffffffu, l[1], 2);
            i0 = rcp_fast(l[0]); i1 = rcp_fast(l[1]);
            ob = slab + mrow * 128;
            it++;
            if (!nxt) break;
            {
              float qa[64];
              const uint32_t s0 = r.stage; mbar_wait(full + 8 * r.stage, r.phase); r.advance();
              issue_qproj<true>(qa, base + s0 * STAGE, wg);
              const uint32_t s1 = r.stage; mbar_wait(full + 8 * r.stage, r.phase); r.advance();
              wgmma_wait<1>(); fence_regs(o);
              release_stage(empty + 8 * vst, lane);
              issue_qproj<false>(qa, base + s1 * STAGE, wg);
              const uint32_t s2 = r.stage; mbar_wait(full + 8 * r.stage, r.phase); r.advance();
              stage_o<0, 2>(o, i0, i1, ob, mrow, lane);
              wgmma_wait<1>();
              release_stage(empty + 8 * s0, lane);
              issue_qproj<false>(qa, base + s2 * STAGE, wg);
              const uint32_t s3 = r.stage; mbar_wait(full + 8 * r.stage, r.phase); r.advance();
              stage_o<2, 2>(o, i0, i1, ob, mrow, lane);
              wgmma_wait<1>();
              release_stage(empty + 8 * s1, lane);
              issue_qproj<false>(qa, base + s3 * STAGE, wg);
              const uint32_t s4 = r.stage; mbar_wait(full + 8 * r.stage, r.phase); r.advance();
              stage_o<4, 2>(o, i0, i1, ob, mrow, lane);
              wgmma_wait<1>();
              release_stage(empty + 8 * s2, lane);
              issue_qproj<false>(qa, base + s4 * STAGE, wg);
              mbar_wait(tail_free, tail_phase ^ 1);
              stage_o<6, 2>(o, i0, i1, ob, mrow, lane);
              wgmma_wait<1>();
              release_stage(empty + 8 * s3, lane);
              fence_async_smem();
              __syncwarp();
              if (lane == 0) mbar_arrive(staged);
              finish_qproj(qa, q, 5, empty + 8 * s4, r, base, full, empty, wg, lane);
            }
          }
        }
        if ((w & 7) == T_END) {
          wgmma_wait<0>(); fence_regs(o);
          release_stage(empty + 8 * vst, lane);
          stage_o<0>(o, i0, i1, ob, mrow, lane);
          stage_o<4>(o, i0, i1, ob, mrow, lane);
          fence_async_smem();
          __syncwarp();
          if (lane == 0) mbar_arrive(staged);
          break;
        }
        const bool ta = (w & 7) == T_OWN;
        const uint32_t s0 = r.stage; mbar_wait(full + 8 * r.stage, r.phase); r.advance();
        if (ta) issue_chunk<1, true>(acc, base + s0 * STAGE, wg); else issue_chunk<0, true>(acc, base + s0 * STAGE, wg);
        const uint32_t s1 = r.stage; mbar_wait(full + 8 * r.stage, r.phase); r.advance();
        wgmma_wait<1>(); fence_regs(o); fence_p(pb);
        release_stage(empty + 8 * vst, lane);
        if (ta) issue_chunk<1, false>(acc, base + s1 * STAGE, wg); else issue_chunk<0, false>(acc, base + s1 * STAGE, wg);
        const uint32_t s2 = r.stage; mbar_wait(full + 8 * r.stage, r.phase); r.advance();
        stage_o<0>(o, i0, i1, ob, mrow, lane);
        wgmma_wait<1>();
        release_stage(empty + 8 * s0, lane);
        if (ta) issue_chunk<1, false>(acc, base + s2 * STAGE, wg); else issue_chunk<0, false>(acc, base + s2 * STAGE, wg);
        stage_o<4>(o, i0, i1, ob, mrow, lane);
        fence_async_smem();
        __syncwarp();
        if (lane == 0) mbar_arrive(staged);
        wgmma_wait<1>();
        release_stage(empty + 8 * s1, lane);
        wgmma_wait<0>(); fence_regs(acc);
        release_stage(empty + 8 * s2, lane);
        r.advance();
        cdone = STG_DELAY;
      } else {
        zero_regs(acc);
      }
      {
        const int type = w & 7, a = (w >> 3) & 31, c0 = (w >> 11) & 127, c1 = (w >> 18) & 127, e = (w >> 25) & 3;
        uint32_t t[40];
        const int brow = min(a * 256 + rank * 128 + wg * 64 + warp * 16 + (lane >> 2), (type == T_MLP1 ? FF : SEQ) - 9);
        const unsigned short* bias = (const unsigned short*)(type == T_MLP1 ? P.b1 : P.b2) + brow;
        prefetch_l1(bias);
        if (type == T_MLP1) {
          const uint32_t last = gemm_loop<1, false>(acc, t, 0, r, 32 - cdone, base, full, empty, wg, lane);
          const uint32_t b0 = bias[0] * 0x10001u, b1 = bias[8] * 0x10001u;
          wgmma_wait<0>(); fence_regs(acc);
          release_stage(last, lane);
#pragma unroll
          for (int j = 0; j < 40; j++) t[j] = bf2_add(pack_bf16(acc[2*j], acc[2*j+1]), (j & 1) ? b1 : b0);
#pragma unroll 1
          for (int k = 0; k < 4; k++) act_step<10, true>(t);
        } else if (type == T_PART) {
          const uint32_t last = gemm_loop<0, false>(acc, t, 0, r, c1 - c0 - cdone, base, full, empty, wg, lane);
          wgmma_wait<0>(); fence_regs(acc);
          release_stage(last, lane);
#pragma unroll
          for (int j = 0; j < 40; j++) t[j] = pack_bf16(acc[2*j], acc[2*j+1]);
        } else {
          float s[80];
          uint32_t last = gemm_loop<1, false>(acc, t, 0, r, 27 - cdone, base, full, empty, wg, lane);
          const uint32_t s0 = r.stage; mbar_wait(full + 8 * r.stage, r.phase); r.advance();
          issue_chunk<0, true>(s, base + s0 * STAGE, wg);
          const uint32_t b0 = bias[0] * 0x10001u, b1 = bias[8] * 0x10001u;
          const uint32_t s1 = r.stage; mbar_wait(full + 8 * r.stage, r.phase); r.advance();
          wgmma_wait<1>(); fence_regs(acc);
          release_stage(last, lane);
          issue_chunk<0, false>(s, base + s1 * STAGE, wg);
          mbar_wait(full + 8 * r.stage, r.phase);
#pragma unroll
          for (int j = 0; j < 40; j++) t[j] = bf2_add(pack_bf16(acc[2*j], acc[2*j+1]), (j & 1) ? b1 : b0);
          wgmma_wait<1>();
          release_stage(empty + 8 * s0, lane);
          last = gemm_loop<0, true>(s, t, empty + 8 * s1, r, 40 / ACT_NR, base, full, empty, wg, lane);
          last = gemm_loop<0, false, 2>(s, t, last, r, c1 - c0 - 2 - 40 / ACT_NR, base, full, empty, wg, lane);
          wgmma_wait<0>(); fence_regs(s);
          release_stage(last, lane);
          if (wg == 1) r.advance();
          const Ring rx = r;
#pragma unroll 1
          for (int q = 0; q < e; q++) {
            r.advance(); r.advance();
            mbar_wait(full + 8 * r.stage, r.phase);
            const uint32_t pb = tile_addr(base + r.stage * STAGE, warp, lane);
#pragma unroll
            for (int k = 0; k < 10; k++) {
              uint32_t v[4];
              ldmatrix_x4((pb ^ ((k & 1) << 5)) + (k >> 1) * 4096, v[0], v[1], v[2], v[3]);
#pragma unroll
              for (int i = 0; i < 4; i++) { s[8*k+2*i] += bf_lo(v[i]); s[8*k+2*i+1] += bf_hi(v[i]); }
            }
          }
          mbar_wait(full + 8 * rx.stage, rx.phase);
          const uint32_t xb = tile_addr(base + rx.stage * STAGE, warp, lane);
#pragma unroll
          for (int k = 0; k < 10; k++) {
            const uint32_t addr = (xb ^ ((k & 1) << 5)) + (k >> 1) * 4096;
            uint32_t v[4];
            ldmatrix_x4(addr, v[0], v[1], v[2], v[3]);
#pragma unroll
            for (int i = 0; i < 4; i++) v[i] = bf2_add(v[i], bf2_mul(pack_bf16(s[8*k+2*i], s[8*k+2*i+1]), t[4*k+i]));
            stmatrix_x4(addr, v[0], v[1], v[2], v[3]);
          }
          fence_async_smem();
          bar_sync(4 + wg, 128);
          if (warp == 0 && elect_one()) {
            tma_store_3d(&P.out_st, base + rx.stage * STAGE, 0, a * 256 + rank * 128 + wg * 64, ((w >> 8) & 7) * 5);
            bulk_commit();
            bulk_wait_read<0>();
          }
          break;
        }
        stage_tile(t, r, base, full, staged, wg, warp, lane);
      }
    }
    __syncwarp();
    cluster_arrive_relaxed(); cluster_wait();
  }
}

typedef CUresult (*EncodeFn)(CUtensorMap*, CUtensorMapDataType, cuuint32_t, void*, const cuuint64_t*, const cuuint64_t*, const cuuint32_t*, const cuuint32_t*,
                             CUtensorMapInterleave, CUtensorMapSwizzle, CUtensorMapL2promotion, CUtensorMapFloatOOBfill);
static void make_map(EncodeFn fn, CUtensorMap* m, const void* ptr, uint64_t inner, uint64_t outer, uint32_t box_inner, uint32_t box_outer) {
  cuuint64_t dims[2] = {inner, outer}; cuuint64_t strides[1] = {inner * 2}; cuuint32_t box[2] = {box_inner, box_outer}; cuuint32_t es[2] = {1, 1};
  fn(m, CU_TENSOR_MAP_DATA_TYPE_BFLOAT16, 2, (void*)ptr, dims, strides, box, es, CU_TENSOR_MAP_INTERLEAVE_NONE, CU_TENSOR_MAP_SWIZZLE_128B,
     CU_TENSOR_MAP_L2_PROMOTION_L2_256B, CU_TENSOR_MAP_FLOAT_OOB_FILL_NONE);
}
static void make_map_b(EncodeFn fn, CUtensorMap* m, const void* ptr, uint64_t rows, uint32_t box_rows = 32) {
  cuuint64_t dims[3] = {32, rows, DM / 32}; cuuint64_t strides[2] = {DM * 2, 64}; cuuint32_t box[3] = {32, box_rows, 5}; cuuint32_t es[3] = {1, 1, 1};
  fn(m, CU_TENSOR_MAP_DATA_TYPE_BFLOAT16, 3, (void*)ptr, dims, strides, box, es, CU_TENSOR_MAP_INTERLEAVE_NONE, CU_TENSOR_MAP_SWIZZLE_64B,
     CU_TENSOR_MAP_L2_PROMOTION_L2_256B, CU_TENSOR_MAP_FLOAT_OOB_FILL_NONE);
}
static inline uint32_t item(int type, int a, int b, int c0 = 0, int c1 = 0, int e = 0) { return type | a << 3 | b << 8 | c0 << 11 | c1 << 18 | e << 25; }
static void build_schedule(uint32_t (&sched)[NCL][MAXI]) {
  int n[NCL];
  for (int c = 0; c < NCL; c++) { n[c] = 0; for (int i = 0; i < MAXI; i++) sched[c][i] = T_END; }
  int m1 = 0;
  for (int c = ZEND; c < 66; c++, m1++) sched[c][n[c]++] = item(T_MLP1, m1 >> 2, m1 & 3);
  for (int i = 1; i < XM; i++) for (int c = 58; c < 66; c++, m1++) sched[c][n[c]++] = item(T_MLP1, m1 >> 2, m1 & 3);
  const int Z = 0, Y = 1, X = 2, lo[3] = {0, ZEND, 58}, hi[3] = {ZEND, 58, 66};
  const int order[11] = {Z, Y, Z, X, Y, Z, X, Y, Z, X, Y};
  int u = 0;
  for (int g = 0; g < 11; g++)
    for (int c = lo[order[g]]; c < hi[order[g]]; c++, u++) sched[c][n[c]++] = item(T_ATT, u >> 3, u & 7);
  int np[32] = {0}, done[32] = {0};
  auto part = [&](int c, int tile, int len) {
    sched[c][n[c]++] = item(T_PART, tile >> 2, tile & 3, done[tile], done[tile] + len, np[tile]++);
    done[tile] += len;
  };
  for (int k = 0; k < 8; k++) { part(32 + k, 8 + k / 2, DB); part(32 + k, k, DA); }
  for (int k = 0; k < 12; k++) { part(40 + k / 2, 12 + k, DZ); part(ZEND + k, 12 + k, DY); }
  for (int k = 0; k < 8; k++) part(58 + k, 24 + k, DX);
  for (int t = 0; t < 32; t++) sched[t][n[t]++] = item(T_OWN, t >> 2, t & 3, done[t], 64, np[t]);
}
extern "C" void kernel_launch(void* const* d_in, const int* in_sizes, int n_in, void* d_out, int out_size) {
  void* fnp = nullptr; cudaDriverEntryPointQueryResult qr;
  cudaGetDriverEntryPoint("cuTensorMapEncodeTiled", &fnp, cudaEnableDefault, &qr);
  EncodeFn fn = (EncodeFn)fnp;
  void *xn, *h, *o, *ut;
  cudaGetSymbolAddress(&xn, g_xn); cudaGetSymbolAddress(&h, g_h); cudaGetSymbolAddress(&o, g_o); cudaGetSymbolAddress(&ut, g_ut);
  Params p;
  make_map(fn, &p.xn, xn, DM, SEQ, 64, 128);
  make_map(fn, &p.wq, d_in[3], NH * DH, DM, 64, 64);
  make_map(fn, &p.k, d_in[1], DH, NH * SEQ, 64, 64);
  make_map(fn, &p.v, d_in[2], DH, NH * SEQ, 64, 64);
  make_map(fn, &p.o, o, NH * DH, SEQ, 64, 128);
  {
    cuuint64_t dims[3] = {64, SEQ, NH * 2}; cuuint64_t strides[2] = {NH * DH * 2, 128}; cuuint32_t box[3] = {64, 16, 2}; cuuint32_t es[3] = {1, 1, 1};
    fn(&p.o_st, CU_TENSOR_MAP_DATA_TYPE_BFLOAT16, 3, o, dims, strides, box, es, CU_TENSOR_MAP_INTERLEAVE_NONE, CU_TENSOR_MAP_SWIZZLE_128B,
       CU_TENSOR_MAP_L2_PROMOTION_L2_256B, CU_TENSOR_MAP_FLOAT_OOB_FILL_NONE);
  }
  make_map(fn, &p.w1, d_in[6], FF, SEQ, 64, 64);
  make_map(fn, &p.w2, d_in[8], SEQ, FF, 64, 64);
  make_map_b(fn, &p.wo, d_in[4], NH * DH);
  make_map_b(fn, &p.h, h, SEQ);
  make_map_b(fn, &p.ut, ut, FF);
  make_map_b(fn, &p.ut_st, ut, FF, 64);
  make_map_b(fn, &p.out_st, d_out, SEQ, 64);
  make_map_b(fn, &p.x_ld, d_in[0], SEQ, 64);
  p.x = (const bf16*)d_in[0]; p.b1 = (const bf16*)d_in[7]; p.b2 = (const bf16*)d_in[9];
  build_schedule(p.sched);
  for (int c = 0, z = 0, y = ZEND, x = 58, k = 0; c < NCL; c++) {
    const bool late = c % 3 == 1 && c != 31 && c != 64;
    if (late) { p.perm[c] = k % 5 == 1 || k % 5 == 3 ? x++ : y++; k++; } else p.perm[c] = z++;
  }
  cudaFuncSetAttribute(fused_kernel, cudaFuncAttributeMaxDynamicSharedMemorySize, SMEM_BYTES);
  fused_kernel<<<2 * NCL, 384, SMEM_BYTES, cudaStreamPerThread>>>(p);
}
```
